```python
import torch

def _softmax(x, axis=-1):
    return torch.softmax(x, dim=axis)
def _gelu(x):
    return torch.nn.functional.gelu(x, approximate="tanh")
def _silu(x):
    return torch.nn.functional.silu(x)
def _sigmoid(x):
    return torch.sigmoid(x)
def _layernorm(x, axis=-1, eps=1e-5):
    m = x.mean(dim=axis, keepdim=True)
    v = x.var(dim=axis, keepdim=True, unbiased=False)
    return (x - m) / torch.sqrt(v + eps)
def _scatter_add(tgt, idx, src, axis=0):
    return tgt.clone().index_add_(axis, idx, src)
def _segment_sum(src, seg, n):
    out = torch.zeros((n,) + src.shape[1:], dtype=src.dtype)
    return out.index_add_(0, seg, src)
def _pad(x, pw):
    flat = tuple(v for pair in reversed(pw) for v in pair)
    return torch.nn.functional.pad(x, flat)

kernel_name = 'standalone__cross_network_dcn__recsys'

def setup_inputs():

    _w = (lambda a: (lambda t: t.to(torch.bfloat16) if t.is_floating_point() else t)(torch.as_tensor(a)))
    B, F, D, L = 16384, 100, 16, 6
    Din = min(F * D, 1024)
    return {
        "x0": _w((lambda *s: torch.randn(*s, dtype=torch.bfloat16) * 0.05)(B, Din)),
        "ws": _w((lambda *s: torch.randn(*s, dtype=torch.bfloat16) * 0.8)(L, Din, Din) * (Din ** -0.5)),
        "bs": _w((lambda *s: torch.randn(*s, dtype=torch.bfloat16) * 3.2)(L, Din) * 0.01),
    }

def reference(x0, ws, bs):
    x = x0
    L = ws.shape[0]
    for l in range(L):
        proj = torch.einsum('bd,de->be', x, ws[l]) + bs[l]
        x = x0 * proj + x
    return x
```

```cpp
#include <cuda_runtime.h>
#include <cuda.h>
#include <cuda_bf16.h>
#include <stdint.h>

namespace dcn {

template <int TA, int TB> __device__ __forceinline__ void wgmma_ss_n256(float (&d)[128], uint64_t da, uint64_t db) {
  asm volatile("{\n.reg .pred p;\nsetp.ne.b32 p, %130, 0;\n"
    "wgmma.mma_async.sync.aligned.m64n256k16.f32.bf16.bf16 "
    "{%0, %1, %2, %3, %4, %5, %6, %7, %8, %9, %10, %11, %12, %13, %14, %15, %16, %17, %18, %19, %20, %21, %22, %23, %24, %25, %26, %27, %28, %29, %30, %31, %32, %33, %34, %35, %36, %37, %38, %39, %40, %41, %42, %43, %44, %45, %46, %47, %48, %49, %50, %51, %52, %53, %54, %55, %56, %57, %58, %59, %60, %61, %62, %63, %64, %65, %66, %67, %68, %69, %70, %71, %72, %73, %74, %75, %76, %77, %78, %79, %80, %81, %82, %83, %84, %85, %86, %87, %88, %89, %90, %91, %92, %93, %94, %95, %96, %97, %98, %99, %100, %101, %102, %103, %104, %105, %106, %107, %108, %109, %110, %111, %112, %113, %114, %115, %116, %117, %118, %119, %120, %121, %122, %123, %124, %125, %126, %127}, "
    "%128, %129, p, 1, 1, %131, %132;\n}\n"
    : "+f"(d[0]), "+f"(d[1]), "+f"(d[2]), "+f"(d[3]), "+f"(d[4]), "+f"(d[5]), "+f"(d[6]), "+f"(d[7]), "+f"(d[8]), "+f"(d[9]), "+f"(d[10]), "+f"(d[11]), "+f"(d[12]), "+f"(d[13]), "+f"(d[14]), "+f"(d[15]), "+f"(d[16]), "+f"(d[17]), "+f"(d[18]), "+f"(d[19]), "+f"(d[20]), "+f"(d[21]), "+f"(d[22]), "+f"(d[23]), "+f"(d[24]), "+f"(d[25]), "+f"(d[26]), "+f"(d[27]), "+f"(d[28]), "+f"(d[29]), "+f"(d[30]), "+f"(d[31]), "+f"(d[32]), "+f"(d[33]), "+f"(d[34]), "+f"(d[35]), "+f"(d[36]), "+f"(d[37]), "+f"(d[38]), "+f"(d[39]), "+f"(d[40]), "+f"(d[41]), "+f"(d[42]), "+f"(d[43]), "+f"(d[44]), "+f"(d[45]), "+f"(d[46]), "+f"(d[47]), "+f"(d[48]), "+f"(d[49]), "+f"(d[50]), "+f"(d[51]), "+f"(d[52]), "+f"(d[53]), "+f"(d[54]), "+f"(d[55]), "+f"(d[56]), "+f"(d[57]), "+f"(d[58]), "+f"(d[59]), "+f"(d[60]), "+f"(d[61]), "+f"(d[62]), "+f"(d[63]), "+f"(d[64]), "+f"(d[65]), "+f"(d[66]), "+f"(d[67]), "+f"(d[68]), "+f"(d[69]), "+f"(d[70]), "+f"(d[71]), "+f"(d[72]), "+f"(d[73]), "+f"(d[74]), "+f"(d[75]), "+f"(d[76]), "+f"(d[77]), "+f"(d[78]), "+f"(d[79]), "+f"(d[80]), "+f"(d[81]), "+f"(d[82]), "+f"(d[83]), "+f"(d[84]), "+f"(d[85]), "+f"(d[86]), "+f"(d[87]), "+f"(d[88]), "+f"(d[89]), "+f"(d[90]), "+f"(d[91]), "+f"(d[92]), "+f"(d[93]), "+f"(d[94]), "+f"(d[95]), "+f"(d[96]), "+f"(d[97]), "+f"(d[98]), "+f"(d[99]), "+f"(d[100]), "+f"(d[101]), "+f"(d[102]), "+f"(d[103]), "+f"(d[104]), "+f"(d[105]), "+f"(d[106]), "+f"(d[107]), "+f"(d[108]), "+f"(d[109]), "+f"(d[110]), "+f"(d[111]), "+f"(d[112]), "+f"(d[113]), "+f"(d[114]), "+f"(d[115]), "+f"(d[116]), "+f"(d[117]), "+f"(d[118]), "+f"(d[119]), "+f"(d[120]), "+f"(d[121]), "+f"(d[122]), "+f"(d[123]), "+f"(d[124]), "+f"(d[125]), "+f"(d[126]), "+f"(d[127])
    : "l"(da), "l"(db), "n"(1), "n"(TA), "n"(TB));
}

constexpr int kDim = 1024;
constexpr int kRows = 16384;
constexpr int kLayers = 6;
constexpr int kGroups = 32;
constexpr int kRounds = kRows / 128 / kGroups;
constexpr int kTiles = kRounds * kLayers;

constexpr float kOffset = 171.f / 256.f;
constexpr int kJobs = kGroups;
constexpr int kEpoch = 32;
constexpr int NA = 4;
constexpr int NB = 9;
constexpr int BPRE = 4;
constexpr int A_SLOT = 8192;
constexpr int B_SLOT = 16384;
constexpr int OFF_B = 0;
constexpr int OFF_A = OFF_B + NB * B_SLOT;
constexpr int OFF_EXTRA = OFF_A + 2 * NA * A_SLOT;
constexpr int OFF_BIAS = OFF_EXTRA + A_SLOT;
constexpr int OFF_INIT = OFF_BIAS + kLayers * 256 * 2;
constexpr int OFF_BAR = OFF_INIT + 16;
constexpr int BAR_BFULL = OFF_BAR;
constexpr int BAR_BEMPTY = BAR_BFULL + NB * 8;
constexpr int BAR_AFULL = BAR_BEMPTY + NB * 8;
constexpr int BAR_AEMPTY = BAR_AFULL + 2 * NA * 8;
constexpr int BAR_XREADY = BAR_AEMPTY + 2 * NA * 8;
constexpr int BAR_PUB = BAR_XREADY + 16;
constexpr int BAR_EXTRA = BAR_PUB + 16;
constexpr int BAR_STAGED = BAR_EXTRA + 16;
constexpr int BAR_ORDER = BAR_STAGED + 2 * NA * 8;
constexpr int BAR_BIAS = BAR_ORDER + 8;
constexpr int SMEM_BYTES = BAR_BIAS + 8;
static_assert(SMEM_BYTES <= 232448, "shared memory budget");

constexpr int kFlagSet = 4 * (kGroups + 1) * 2 * 32;
__device__ unsigned int g_flags[2 * kFlagSet];

__device__ __forceinline__ uint32_t smem_u32(const void* p) { return (uint32_t)__cvta_generic_to_shared(p); }
__device__ __forceinline__ void mbar_init(uint32_t bar, int cnt) {
  asm volatile("mbarrier.init.shared::cta.b64 [%0], %1;" ::"r"(bar), "r"(cnt) : "memory");
}
__device__ __forceinline__ void mbar_arrive(uint32_t bar) {
  asm volatile("mbarrier.arrive.shared::cta.b64 _, [%0];" ::"r"(bar) : "memory");
}
__device__ __forceinline__ uint32_t map_cta(uint32_t addr, uint32_t cta) {
  uint32_t r;
  asm volatile("mapa.shared::cluster.u32 %0, %1, %2;" : "=r"(r) : "r"(addr), "r"(cta));
  return r;
}
__device__ __forceinline__ void mbar_arrive_mapped(uint32_t cluster_addr) {
  asm volatile("mbarrier.arrive.shared::cluster.b64 _, [%0];" ::"r"(cluster_addr) : "memory");
}
__device__ __forceinline__ void mbar_wait(uint32_t bar, uint32_t parity) {
  asm volatile(
      "{\n.reg .pred p;\n.reg .u32 c;\n"
      "mbarrier.try_wait.parity.shared::cta.b64 p, [%0], %1;\n"
      "@p bra DONE;\n"
      "mov.u32 c, 0;\n"
      "LOOP:\n"
      "mbarrier.try_wait.parity.shared::cta.b64 p, [%0], %1;\n"
      "@p bra DONE;\n"
      "add.u32 c, c, 1;\n"
      "setp.lt.u32 p, c, 4194304;\n"
      "@p bra LOOP;\n"
      "trap;\n"
      "DONE:\n}"
      ::"r"(bar), "r"(parity) : "memory");
}
__device__ __forceinline__ void mbar_spin(uint32_t bar, uint32_t parity) {
  asm volatile(
      "{\n.reg .pred p;\n"
      "LOOP:\n"
      "mbarrier.try_wait.parity.shared::cta.b64 p, [%0], %1;\n"
      "@!p bra LOOP;\n}"
      ::"r"(bar), "r"(parity) : "memory");
}
#define ELECT_BEGIN "{\n.reg .pred e;\nelect.sync _|e, 0xffffffff;\n"
template <bool STREAM> __device__ __forceinline__ void expect_load_2d_e(uint32_t dst, const CUtensorMap* m, uint32_t bar, int c0, int c1) {
  if (STREAM) {
    asm volatile(ELECT_BEGIN ".reg .b64 pol;\ncreatepolicy.fractional.L2::evict_first.b64 pol, 1.0;\n"
                 "@e mbarrier.arrive.expect_tx.shared::cta.b64 _, [%2], 8192;\n"
                 "@e cp.async.bulk.tensor.2d.shared::cluster.global.mbarrier::complete_tx::bytes.L2::cache_hint [%0], [%1, {%3, %4}], [%2], pol;\n}"
                 ::"r"(dst), "l"(m), "r"(bar), "r"(c0), "r"(c1) : "memory");
  } else {
    asm volatile(ELECT_BEGIN
                 "@e mbarrier.arrive.expect_tx.shared::cta.b64 _, [%2], 8192;\n"
                 "@e cp.async.bulk.tensor.2d.shared::cluster.global.mbarrier::complete_tx::bytes [%0], [%1, {%3, %4}], [%2];\n}"
                 ::"r"(dst), "l"(m), "r"(bar), "r"(c0), "r"(c1) : "memory");
  }
}
__device__ __forceinline__ void expect_load_2d_mc_e(uint32_t dst, const CUtensorMap* m, uint32_t bar, int c0, int c1) {
  asm volatile(ELECT_BEGIN ".reg .b64 pol;\ncreatepolicy.fractional.L2::evict_first.b64 pol, 1.0;\n"
               "@e mbarrier.arrive.expect_tx.shared::cta.b64 _, [%2], 8192;\n"
               "@e cp.async.bulk.tensor.2d.shared::cluster.global.mbarrier::complete_tx::bytes.multicast::cluster.L2::cache_hint [%0], [%1, {%3, %4}], [%2], %5, pol;\n}"
               ::"r"(dst), "l"(m), "r"(bar), "r"(c0), "r"(c1), "h"((uint16_t)3) : "memory");
}
__device__ __forceinline__ void expect_load_3d_e(uint32_t dst, const CUtensorMap* m, uint32_t bar, int c0, int c1, int c2) {
  asm volatile(ELECT_BEGIN
               "@e mbarrier.arrive.expect_tx.shared::cta.b64 _, [%2], 16384;\n"
               "@e cp.async.bulk.tensor.3d.shared::cluster.global.mbarrier::complete_tx::bytes [%0], [%1, {%3, %4, %5}], [%2];\n}"
               ::"r"(dst), "l"(m), "r"(bar), "r"(c0), "r"(c1), "r"(c2) : "memory");
}
template <bool STREAM> __device__ __forceinline__ void store_2d_e(const CUtensorMap* m, uint32_t src, int c0, int c1) {
  if (STREAM) {
    asm volatile(ELECT_BEGIN ".reg .b64 pol;\ncreatepolicy.fractional.L2::evict_first.b64 pol, 1.0;\n"
                 "@e cp.async.bulk.tensor.2d.global.shared::cta.bulk_group.L2::cache_hint [%0, {%2, %3}], [%1], pol;\n}"
                 ::"l"(m), "r"(src), "r"(c0), "r"(c1) : "memory");
  } else {
    asm volatile(ELECT_BEGIN
                 "@e cp.async.bulk.tensor.2d.global.shared::cta.bulk_group [%0, {%2, %3}], [%1];\n}"
                 ::"l"(m), "r"(src), "r"(c0), "r"(c1) : "memory");
  }
}
__device__ __forceinline__ void prefetch_2d_e(const CUtensorMap* m, int c0, int c1) {
  asm volatile(ELECT_BEGIN
               "@e cp.async.bulk.prefetch.tensor.2d.L2.global [%0, {%1, %2}];\n}"
               ::"l"(m), "r"(c0), "r"(c1) : "memory");
}
__device__ __forceinline__ void prefetch_1d_e(const void* ptr, uint32_t bytes) {
  asm volatile(ELECT_BEGIN
               "@e cp.async.bulk.prefetch.L2.global [%0], %1;\n}"
               ::"l"(ptr), "r"(bytes) : "memory");
}
__device__ __forceinline__ void grid_load_3d_e(uint32_t dst, const CUtensorMap* m, uint32_t bar, int c0, int c1, int c2) {
  asm volatile(ELECT_BEGIN
               ".reg .pred p;\n.reg .u32 a, b;\n.reg .u64 c;\n"
               "mov.u64 c, %%clock64;\ncvt.u32.u64 a, c;\n"
               "@e mbarrier.arrive.expect_tx.shared::cta.b64 _, [%2], 16384;\n"
               "EDGE:\n"
               "mov.u64 c, %%clock64;\ncvt.u32.u64 b, c;\n"
               "xor.b32 b, b, a;\n"
               "setp.lt.u32 p, b, 512;\n"
               "@p bra.uni EDGE;\n"
               "@e cp.async.bulk.tensor.3d.shared::cluster.global.mbarrier::complete_tx::bytes [%0], [%1, {%3, %4, %5}], [%2];\n}"
               ::"r"(dst), "l"(m), "r"(bar), "r"(c0), "r"(c1), "r"(c2) : "memory");
}
__device__ __forceinline__ void arrive_mapped_e(uint32_t cluster_addr) {
  asm volatile(ELECT_BEGIN "@e mbarrier.arrive.shared::cluster.b64 _, [%0];\n}" ::"r"(cluster_addr) : "memory");
}
__device__ __forceinline__ void arrive_e(uint32_t bar) {
  asm volatile(ELECT_BEGIN "@e mbarrier.arrive.shared::cta.b64 _, [%0];\n}" ::"r"(bar) : "memory");
}
__device__ __forceinline__ void bulk_commit() { asm volatile("cp.async.bulk.commit_group;" ::: "memory"); }
template <int N> __device__ __forceinline__ void bulk_wait() { asm volatile("cp.async.bulk.wait_group %0;" ::"n"(N) : "memory"); }
__device__ __forceinline__ void wg_fence() { asm volatile("wgmma.fence.sync.aligned;" ::: "memory"); }
__device__ __forceinline__ void wg_commit() { asm volatile("wgmma.commit_group.sync.aligned;" ::: "memory"); }
template <int N> __device__ __forceinline__ void wg_wait() { asm volatile("wgmma.wait_group.sync.aligned %0;" ::"n"(N) : "memory"); }
__device__ __forceinline__ void fence_async_global() { asm volatile("fence.proxy.async.global;" ::: "memory"); }
__device__ __forceinline__ void st_relaxed(unsigned int* p, unsigned int v) {
  asm volatile("st.relaxed.gpu.global.u32 [%0], %1;" ::"l"(p), "r"(v) : "memory");
}
__device__ __forceinline__ unsigned int ld_acquire(const unsigned int* p) {
  unsigned int v;
  asm volatile("ld.acquire.gpu.global.u32 %0, [%1];" : "=r"(v) : "l"(p) : "memory");
  return v;
}
__device__ __forceinline__ void ldsm4(uint32_t* r, uint32_t addr) {
  asm volatile("ldmatrix.sync.aligned.m8n8.x4.shared.b16 {%0, %1, %2, %3}, [%4];"
               : "=r"(r[0]), "=r"(r[1]), "=r"(r[2]), "=r"(r[3]) : "r"(addr) : "memory");
}
__device__ __forceinline__ void stsm4(uint32_t addr, const uint32_t* r) {
  asm volatile("stmatrix.sync.aligned.m8n8.x4.shared.b16 [%0], {%1, %2, %3, %4};"
               ::"r"(addr), "r"(r[0]), "r"(r[1]), "r"(r[2]), "r"(r[3]) : "memory");
}
__device__ __forceinline__ void load_partial(float* a, uint32_t addr) {
  asm volatile("ld.shared.v4.f32 {%0, %1, %2, %3}, [%4];"
               : "+f"(a[4]), "+f"(a[5]), "+f"(a[6]), "+f"(a[7]) : "r"(addr) : "memory");
}
__device__ __forceinline__ void widen_partial(float* a) {
  asm volatile("shl.b32 %0, %4, 16;\nand.b32 %1, %4, 0xffff0000;\n"
               "shl.b32 %2, %5, 16;\nand.b32 %3, %5, 0xffff0000;\n"
               "shl.b32 %4, %6, 16;\nand.b32 %5, %6, 0xffff0000;\n"
               "shl.b32 %6, %7, 16;\nand.b32 %7, %7, 0xffff0000;"
               : "+f"(a[0]), "+f"(a[1]), "+f"(a[2]), "+f"(a[3]), "+f"(a[4]), "+f"(a[5]), "+f"(a[6]), "+f"(a[7]));
}
template <bool V> struct Flag { static constexpr bool value = V; };
__device__ __forceinline__ void fence_async_smem() { asm volatile("fence.proxy.async.shared::cta;" ::: "memory"); }
__device__ __forceinline__ void cluster_arrive_relaxed() { asm volatile("barrier.cluster.arrive.relaxed.aligned;" ::: "memory"); }
__device__ __forceinline__ void cluster_wait() { asm volatile("barrier.cluster.wait.acquire.aligned;" ::: "memory"); }
__device__ __forceinline__ void prefetch_map(const CUtensorMap* m) {
  asm volatile("prefetch.tensormap [%0];" ::"l"(m) : "memory");
}
__device__ __forceinline__ void poll_flag(const unsigned int* ptr, unsigned int target) {
  asm volatile(
      "{\n.reg .pred p;\n.reg .u32 c;\n.reg .s32 v;\n"
      "mov.u32 c, 0;\n"
      "LOOP:\n"
      "ld.acquire.gpu.global.s32 v, [%0];\n"
      "sub.s32 v, v, %1;\n"
      "setp.ge.s32 p, v, 0;\n"
      "@p bra DONE;\n"
      "add.u32 c, c, 1;\n"
      "setp.lt.u32 p, c, 4194304;\n"
      "@p bra LOOP;\n"
      "trap;\n"
      "DONE:\n}"
      ::"l"(ptr), "r"(target) : "memory");
}

constexpr uint32_t DESC_HI = (1024u >> 4) | (1u << 30);
__device__ __forceinline__ uint64_t desc(uint32_t lo) { return ((uint64_t)DESC_HI << 32) | lo; }
constexpr uint32_t DESC_A_LBO = 1u << 16;
constexpr uint32_t DESC_B_LBO = (4096u >> 4) << 16;

struct Ring {
  uint32_t slot, phase;
  template <int N> __device__ __forceinline__ void next() {
    if (++slot == N) { slot = 0; phase ^= 1; }
  }
};

__device__ __forceinline__ int kgroup_col(int j, int q) {
  return q == 0 ? j : (q == 1 ? (j ^ 1) : (((j ^ 2) & ~1) + (q - 2)));
}

__device__ __forceinline__ int role_of_cluster(int c) {
  const int a = c - 4;
  const int b = c - 36, r = (b * 37) >> 8;
  const int first = (a & ~7) + (a & 3) * 2 + ((a >> 2) & 1);
  const int second = 32 + r * 8 + ((0x7531640 >> (((b - r * 7) * 4) & 31)) & 7);
  return c >= 2 * kGroups ? c : (c >= 36 ? second : (c >= 4 ? first : 34 + c * 8));
}
__device__ __forceinline__ int helped_round(int grp) { return (grp & 2) ? (grp & 3) - 1 : 3; }
__device__ __forceinline__ int job_of_group(int grp) {
  return (grp & 2) ? (grp & 1) * 8 + (grp >> 2) : 16 + (grp >> 2) * 2 + (grp & 1);
}
__device__ __forceinline__ int job_row(int n) {
  const int grp = n < 16 ? (n & 7) * 4 + 2 + (n >> 3) : ((n - 16) >> 1) * 4 + (n & 1);
  return (helped_round(grp) * kGroups + grp) * 128;
}

#define PROF_ENDS(idx) do {} while (0)
#define PROF_SVC(idx) do {} while (0)
#define PROF(idx) do {} while (0)
#define PROF_DUMP() do {} while (0)
constexpr int PROF_SMEM = 0;

__global__ void __cluster_dims__(2, 1, 1) __launch_bounds__(384, 1)
dcn_kernel(const __grid_constant__ CUtensorMap mx64, const __grid_constant__ CUtensorMap mx32,
           const __grid_constant__ CUtensorMap mo64, const __grid_constant__ CUtensorMap mo32,
           const __grid_constant__ CUtensorMap mw, const __nv_bfloat16* __restrict__ xptr,
           const __nv_bfloat16* __restrict__ wptr, const __nv_bfloat16* __restrict__ bias, __nv_bfloat16* optr) {
  extern __shared__ __align__(1024) uint8_t smem_raw[];
  const uint32_t sb = smem_u32(smem_raw);
  const int tid = threadIdx.x;
  if (tid == 256) {
    prefetch_map(&mw);
    prefetch_map(&mx64);
    mbar_init(sb + BAR_BFULL, 1);
    mbar_init(sb + BAR_BFULL + 8, 1);
    mbar_init(sb + BAR_AFULL, 1);
    mbar_init(sb + BAR_AFULL + NA * 8, 1);
    asm volatile("fence.mbarrier_init.release.cluster;" ::: "memory");
  }
  const int wg = __shfl_sync(0xffffffffu, tid >> 7, 0);
  const int warp = __shfl_sync(0xffffffffu, (tid >> 5) & 3, 0);
  const int bid = role_of_cluster(blockIdx.x >> 1) * 2 + (blockIdx.x & 1);
  const int j = bid & 3;
  const int grp = bid >> 2;
  const uint32_t rank = j & 1;
  const bool helper = grp == kGroups;
  const int short_t = (gridDim.x > 4 * kGroups && !helper) ? helped_round(grp) * kLayers : -1;
  if (tid == 0) PROF_ENDS(1000);

  const int col0 = helper ? kgroup_col(j, 2) * 256 : 0;
  const int row0 = helper ? job_row(0) : grp * 128;
  if (tid < 32 && !helper) {
    asm volatile("prefetch.global.L2 [%0];" ::"l"(wptr + (size_t)((grp & 7) * 8 + (tid >> 2)) * kDim + j * 256 + (tid & 3) * 64));
    asm volatile("prefetch.global.L2 [%0];" ::"l"(xptr + (size_t)(row0 + j * 32 + tid) * kDim));
  }
  auto first_loads = [&](int s) {
    const int col = col0 + s * 64;
    expect_load_3d_e(sb + OFF_B + 2 * s * B_SLOT, &mw, sb + BAR_BFULL + 2 * s * 8, 0, col, j * 4);
    expect_load_2d_e<false>(sb + OFF_A + s * A_SLOT, &mx64, sb + BAR_AFULL + s * 8, col, row0);
    expect_load_3d_e(sb + OFF_B + (2 * s + 1) * B_SLOT, &mw, sb + BAR_BFULL + (2 * s + 1) * 8, 0, col + 32, j * 4);
    expect_load_2d_e<false>(sb + OFF_A + (NA + s) * A_SLOT, &mx64, sb + BAR_AFULL + (NA + s) * 8, col, row0 + 64);
  };
  if (wg == 2 && warp == 0) first_loads(0);
  if (tid == 288) {
    if (sb & 1023) asm volatile("trap;");
#pragma unroll
    for (int i = 0; i < NB; i++) mbar_init(sb + BAR_BEMPTY + i * 8, 2);
#pragma unroll
    for (int i = 0; i < 2 * NA; i++) { mbar_init(sb + BAR_AEMPTY + i * 8, 2); mbar_init(sb + BAR_STAGED + i * 8, 4); }
    asm volatile("fence.mbarrier_init.release.cluster;" ::: "memory");
  }
  if (tid == 320) {
#pragma unroll
    for (int i = 2; i < NB; i++) mbar_init(sb + BAR_BFULL + i * 8, 1);
#pragma unroll
    for (int i = 0; i < 2 * NA; i++)
      if (i % NA) mbar_init(sb + BAR_AFULL + i * 8, 1);
#pragma unroll
    for (int i = 0; i < 6; i++) mbar_init(sb + BAR_XREADY + i * 8, 1);
    asm volatile("st.shared.v4.f32 [%0], {%1, %1, %1, %1};" ::"r"(sb + OFF_INIT), "f"(kOffset) : "memory");
    mbar_init(sb + BAR_ORDER, 1);
    mbar_init(sb + BAR_BIAS, 32);
    asm volatile("fence.mbarrier_init.release.cluster;" ::: "memory");
  }
  __syncthreads();
  cluster_arrive_relaxed();

  if (wg == 2) {
    asm volatile("setmaxnreg.dec.sync.aligned.u32 40;");
    if (warp == 0) {
#pragma unroll 1
      for (int s = 1; s < 4; s++) first_loads(s);
      cluster_wait();
      Ring r{8, 1};
      int l = 0;
      const int ntiles = helper ? kJobs : kTiles;
#pragma unroll 1
      for (int t = 0; t < ntiles; t++) {
        const int jo = (t == 0 && !helper) ? 0 : j;
        const int q_end = t == short_t ? 2 : 4;
#pragma unroll 1
        for (int q = (helper ? 2 : 0) + (t == 0); q < q_end; q++) {
          const int krow = l * kDim + kgroup_col(jo, q) * 256;
          if (q < 2 || helper) {
#pragma unroll 1
            for (int k = krow; k != krow + 256; k += 32) {
              mbar_spin(sb + BAR_BEMPTY + r.slot * 8, r.phase);
              expect_load_3d_e(sb + OFF_B + r.slot * B_SLOT, &mw, sb + BAR_BFULL + r.slot * 8, 0, k, j * 4);
              r.next<NB>();
            }
          } else {
#pragma unroll 1
            for (int k = krow; k != krow + 256; k += 32) {
              mbar_spin(sb + BAR_BEMPTY + r.slot * 8, r.phase);
              grid_load_3d_e(sb + OFF_B + r.slot * B_SLOT, &mw, sb + BAR_BFULL + r.slot * 8, 0, k, j * 4);
              r.next<NB>();
            }
          }
        }
        if (helper || ++l == kLayers) l = 0;
      }
    } else if (warp <= 2) {
      const int w = warp - 1;
      const uint32_t abase = sb + OFF_A + w * NA * A_SLOT;
      const uint32_t fullb = sb + BAR_AFULL + w * NA * 8;
      const uint32_t emptyb = sb + BAR_AEMPTY + w * NA * 8;
      const uint32_t stagedb = sb + BAR_STAGED + w * NA * 8;
      const unsigned int base = __shfl_sync(0xffffffffu, *(volatile unsigned int*)(g_flags + (bid * 2 + w) * 32), 0);
      cluster_wait();
      uint32_t epar = 0;
      uint32_t spar = 0;
      auto refill = [&](const CUtensorMap* m, int col, int row) {
#pragma unroll 1
        for (int s = 0; s < 4; s++) {
          mbar_wait(emptyb + s * 8, epar);
          expect_load_2d_e<false>(abase + s * A_SLOT, m, fullb + s * 8, col + s * 64, row);
        }
        epar ^= 1;
      };
      auto store_refill = [&](int out_row, int col, int row, bool last_read) {
#pragma unroll 1
        for (int s = 0; s < 4; s++) {
          mbar_wait(stagedb + s * 8, spar);
          fence_async_smem();
          store_2d_e<true>(&mo64, abase + s * A_SLOT, j * 256 + s * 64, out_row);
          bulk_commit();
          bulk_wait<0>();
          __syncwarp();
          mbar_wait(emptyb + s * 8, epar);
          if (last_read) expect_load_2d_e<true>(abase + s * A_SLOT, &mx64, fullb + s * 8, col + s * 64, row);
          else expect_load_2d_e<false>(abase + s * A_SLOT, &mx64, fullb + s * 8, col + s * 64, row);
        }
        spar ^= 1;
        epar ^= 1;
      };
      auto store_tile = [&](auto stream, int out_row) {
#pragma unroll 1
        for (int c = 0; c < 4; c++) {
          mbar_wait(stagedb + c * 8, spar);
          fence_async_smem();
          store_2d_e<decltype(stream)::value>(&mo64, abase + c * A_SLOT, j * 256 + c * 64, out_row);
        }
        spar ^= 1;
        bulk_commit();
        bulk_wait<0>();
        __syncwarp();
      };
      auto refill_shared = [&](const CUtensorMap* m32, int col, int row) {
#pragma unroll 1
        for (int s = 0; s < 4; s++) {
          mbar_wait(emptyb + s * 8, epar);
          expect_load_2d_mc_e(abase + s * A_SLOT + rank * 4096, m32, fullb + s * 8, col + s * 64, row + rank * 32);
        }
        epar ^= 1;
      };
      if (helper) {
#pragma unroll 1
        for (int h = 1; h < 2 * kJobs; h++) refill_shared(&mx32, col0 + (h & 1) * 256, job_row(h >> 1) + w * 64);
      } else {
        const uint32_t xready_peer = map_cta(sb + BAR_XREADY + w * 8, rank ^ 1);
        const unsigned int* oflag = g_flags + ((grp * 4 + kgroup_col(j, 2)) * 2 + w) * 32;
        unsigned int* done_mine = g_flags + kFlagSet + (bid * 2 + w) * 32;
        const unsigned int* done_peer = g_flags + kFlagSet + ((bid ^ 2) * 2 + w) * 32;
        uint32_t nx = 0;
        uint32_t fpar = 0;
#pragma unroll 1
        for (int rd = 0; rd < kRounds; rd++) {
          const int xrow = (rd * kGroups + grp) * 128 + w * 64;
          if (rd == 0) {
            refill(&mx64, 256, xrow);
          } else {
            poll_flag(done_peer, base + nx);
            store_refill(xrow - kGroups * 128, (j ^ 1) * 256, xrow, rd * kLayers == short_t);
          }
          if (rd * kLayers != short_t) {
#pragma unroll 1
            for (int h = 0; h < 2; h++) refill_shared(&mx32, (kgroup_col(rd == 0 ? 0 : j, 2) + h) * 256, xrow);
          }
          fpar ^= 1;
#pragma unroll 1
          for (int l = 1; l < kLayers; l++) {
            if (l > 1) poll_flag(done_peer, base + nx);
            store_tile(Flag<false>(), xrow);
            PROF_SVC((rd * kLayers + l - 1) * 2 + w);
            arrive_mapped_e(xready_peer);
            arrive_e(sb + BAR_PUB + w * 8);
            mbar_wait(sb + BAR_XREADY + w * 8, nx & 1);
            fence_async_global();
            refill(&mo64, (j ^ 1) * 256, xrow);
            if (rd * kLayers + l + 1 == short_t) {
              poll_flag(g_flags + ((4 * kGroups + j) * 2 + 1) * 32, base + job_of_group(grp) + 1);
              fence_async_global();
              if (w == 0) expect_load_2d_e<false>(sb + OFF_EXTRA, &mo64, sb + BAR_EXTRA, j * 256, xrow + kGroups * 128);
            }
#pragma unroll 1
            for (int h = 0; h < 2; h++) {
              poll_flag(oflag + h * 64, base + nx + 1);
              fence_async_global();
              refill_shared(&mo32, (kgroup_col(j, 2) + h) * 256, xrow);
            }
            fpar ^= 1;
            if (rank) {
#pragma unroll 1
              for (int s = 0; s < 4; s++) mbar_wait(fullb + s * 8, fpar);
            }
            nx++;
            if ((tid & 31) == 0) st_relaxed(done_mine, base + (nx == kRounds * (kLayers - 1) ? kEpoch : nx));
            __syncwarp();
          }
          const int nrow = xrow + kGroups * 128;
          if (rd + 1 == kRounds) {
            poll_flag(done_peer, base + nx);
            store_tile(Flag<true>(), xrow);
          } else if ((rd + 1) * kLayers == short_t) {
#pragma unroll 1
            for (int s = 0; s < 4; s++) {
              mbar_wait(emptyb + s * 8, epar);
              if (s == 0) {
                arrive_e(fullb);
                mbar_wait(fullb, fpar ^ 1);
              }
              expect_load_2d_e<false>(abase + s * A_SLOT, s > 0 ? &mo64 : &mx64, fullb + s * 8, j * 256 + s * 64, nrow);
            }
            epar ^= 1;
#pragma unroll 1
            for (int s = 0; s < 4; s++) {
              mbar_wait(stagedb + s * 8, spar);
              fence_async_smem();
              if (s > 0) expect_load_2d_e<false>(abase + s * A_SLOT, &mx64, fullb + s * 8, j * 256 + s * 64, nrow);
              else if (w == 0) expect_load_2d_e<false>(sb + OFF_EXTRA, &mo64, sb + BAR_EXTRA + 8, j * 256, nrow + 64);
            }
            spar ^= 1;
          } else {
            refill(&mx64, j * 256, nrow);
            fpar ^= 1;
          }
          PROF_SVC((rd * kLayers + kLayers - 1) * 2 + w);
        }
      }
    } else {
      const int lane = tid & 31;
      unsigned int* myflag = g_flags + bid * 2 * 32;
      if (lane == 0) { prefetch_map(&mx32); prefetch_map(&mo64); prefetch_map(&mo32); }
      const unsigned int base = *(volatile unsigned int*)myflag;
      auto publish = [&](uint32_t n, uint32_t value) {
#pragma unroll 1
        for (int w = 0; w < 2; w++) {
          mbar_wait(sb + BAR_PUB + w * 8, n & 1);
          asm volatile("fence.acq_rel.gpu;" ::: "memory");
          if (lane == 0) st_relaxed(myflag + w * 32, base + value);
          __syncwarp();
        }
      };
      if (helper) {
        cluster_wait();
#pragma unroll 1
        for (int n = 0; n < kJobs; n++) {
          if (n + 2 < kJobs) {
            const int row = job_row(n + 2);
#pragma unroll 1
            for (int i = 0; i < 8; i++) prefetch_2d_e(&mx64, col0 + rank * 256 + (i & 3) * 64, row + (i >> 2) * 64);
          }
          publish(n, n + 1);
        }
      } else {
        {
          float c[8];
#pragma unroll
          for (int i = 0; i < 8; i++) c[i] = 1.f - kOffset;
#pragma unroll 1
          for (int l = 0; l < kLayers; l++) {
            const uint4 v = *reinterpret_cast<const uint4*>(bias + l * kDim + j * 256 + lane * 8);
            const uint32_t u[4] = {v.x, v.y, v.z, v.w};
#pragma unroll
            for (int i = 0; i < 4; i++) {
              c[2 * i] += __uint_as_float(u[i] << 16);
              c[2 * i + 1] += __uint_as_float(u[i] & 0xffff0000u);
              uint32_t pk;
              asm("cvt.rn.bf16x2.f32 %0, %1, %2;" : "=r"(pk) : "f"(c[2 * i + 1]), "f"(c[2 * i]));
              asm volatile("st.shared.u32 [%0], %1;" ::"r"(sb + OFF_BIAS + l * 512 + (lane >> 2) * 64 + i * 16 + (lane & 3) * 4),
                           "r"(pk) : "memory");
            }
          }
          mbar_arrive(sb + BAR_BIAS);
        }
        const __nv_bfloat16* wslice = wptr + bid * 8192;
        prefetch_1d_e(wslice + kDim * kDim, 16384);
        cluster_wait();
        uint32_t nx = 0;
#pragma unroll 1
        for (int rd = 0; rd < kRounds; rd++) {
#pragma unroll 1
          for (int l = 1; l < kLayers; l++) {
            publish(nx, nx + 1 == kRounds * (kLayers - 1) ? kEpoch : nx + 1);
            nx++;
            if (l < kLayers - 1) {
              if (rd == 0) prefetch_1d_e(wslice + (l + 1) * kDim * kDim, 16384);
            } else if (rd + 1 < kRounds) {
              const int nrow = ((rd + 1) * kGroups + grp) * 128;
              bool partial = false;
              if ((rd + 1) * kLayers == short_t) {
                const unsigned int v = ld_acquire(g_flags + ((4 * kGroups + j) * 2 + 1) * 32);
                partial = __shfl_sync(0xffffffffu, (int)(v - (base + job_of_group(grp) + 1)) >= 0, 0);
              }
#pragma unroll 1
              for (int i = partial ? 0 : 8; i < 16; i++) {
                prefetch_2d_e(i < 8 ? &mo64 : &mx64, j * 256 + ((i >> 1) & 3) * 64, nrow + (i & 1) * 64);
                __nanosleep(i < 8 ? 100 : 300);
              }
            }
          }
        }
      }
    }
    if (warp == (helper ? 3 : 2) && (tid & 31) == 0) PROF_ENDS(1002);
    if (warp == 2) PROF_DUMP();
  } else {
    asm volatile("setmaxnreg.inc.sync.aligned.u32 232;");
    const int lane = tid & 31;
    const int wtid = tid & 127;
    const uint32_t abase = sb + OFF_A + wg * NA * A_SLOT;
    const uint32_t afull = sb + BAR_AFULL + wg * NA * 8;
    const uint32_t aempty = map_cta(sb + BAR_AEMPTY + wg * NA * 8, wtid == 32 ? (rank ^ 1) : rank);
    const bool rel_a = (wtid == 0) || (wtid == 32);
    const bool rel_b = (wtid == 64);
    const uint32_t frag0 = __shfl_sync(0xffffffffu, abase + ((wtid >> 5) * 16 + ((lane >> 3) & 1) * 8 + (lane & 7)) * 128 +
                                                        (((lane >> 4) ^ (lane & 7)) << 4), lane);
    const uint32_t adesc0 = ((abase & 0x3FFFF) >> 4) | DESC_A_LBO;
    const uint32_t bdesc0 = (((sb + OFF_B) & 0x3FFFF) >> 4) | DESC_B_LBO;

    float acc[128];
    uint32_t xr[64];
#pragma unroll
    for (int i = 0; i < 128; i++) asm volatile("mov.f32 %0, %1;" : "=f"(acc[i]) : "f"(kOffset));
#pragma unroll
    for (int i = 0; i < 64; i++) xr[i] = 0;
    Ring rb{0, 0};
    uint32_t slot_m1 = 0, slot_m2 = 0, slot_m3 = 0;
    uint32_t fpar = 0;
    int l = 0;
    bool hold = false;
    bool swap = false;
    int q_second = helper ? 3 : 1;
    int capture_q = helper ? -1 : j;

    auto release_b = [&](uint32_t slot) {
      if (rel_b) mbar_arrive(sb + BAR_BEMPTY + slot * 8);
    };
    auto release_a = [&](int s) {
      if (rel_a) mbar_arrive_mapped(aempty + s * 8);
    };
    auto chunk_staged = [&](int c) {
      __syncwarp();
      arrive_e(sb + BAR_STAGED + (wg * NA + c) * 8);
    };
    auto capture_slot = [&](int p) {
#pragma unroll
      for (int g = 0; g < 4; g++) ldsm4(&xr[(p * 4 + g) * 4], (frag0 ^ (g * 32)) + p * A_SLOT);
    };
    auto swap_half = [&](int p, int half) {
#pragma unroll
      for (int g = half * 2; g < half * 2 + 2; g++) {
        const uint32_t addr = (frag0 ^ (g * 32)) + p * A_SLOT;
        uint32_t n[4];
        ldsm4(n, addr);
        stsm4(addr, &xr[(p * 4 + g) * 4]);
#pragma unroll
        for (int i = 0; i < 4; i++) xr[(p * 4 + g) * 4 + i] = n[i];
      }
      if (half) chunk_staged(p);
    };
    auto half_step = [&](int q, int s, int h, int t, bool first) {
      if (s == 0 && h == 1 && q == 3 && wg == 1) {
        wg_wait<1>();
        release_b(slot_m2);
        wg_wait<0>();
        release_b(slot_m1);
        if (swap && q_second == 3) { swap_half(3, 0); swap_half(3, 1); }
        release_a(3);
        mbar_spin(sb + BAR_ORDER, t & 1);
      }
      if (!(first && h == 0)) mbar_spin(sb + BAR_BFULL + rb.slot * 8, rb.phase);
      const uint32_t bdesc = bdesc0 + rb.slot * (B_SLOT >> 4);
      const uint32_t adesc = adesc0 + s * (A_SLOT >> 4) + h * 4;
      wg_fence();
      wgmma_ss_n256<0, 1>(acc, desc(adesc), desc(bdesc));
      wgmma_ss_n256<0, 1>(acc, desc(adesc + 2), desc(bdesc + 128));
      wg_commit();
      slot_m3 = slot_m2;
      slot_m2 = slot_m1;
      slot_m1 = rb.slot;
      rb.next<NB>();
      if (s == 3 && h == 1 && q == 3 && wg == 0 && wtid == 96) mbar_arrive(sb + BAR_ORDER);
    };
    auto retire = [&](int q, int s, int h, bool first) {
      if (h == 1 && q == capture_q) capture_slot(s);
      const bool drained = s * 2 + h >= 1 && s * 2 + h <= 2 && q == 3 && wg == 1;
      if (!first && !drained) {
        wg_wait<2>();
        release_b(slot_m3);
        if (h == 1) {
          if (s == 0 || q < 3 || hold) release_a((s + 3) & 3);
          if ((s == 0 || q == 0) && swap && q == (s == 0 ? q_second : 0)) swap_half((s + 3) & 3, 0);
        } else {
          if ((s <= 1) != (q == 0) && swap && q == (s <= 1 ? q_second : 0)) swap_half((s + 2) & 3, 1);
        }
      }
    };

    cluster_wait();
    const int ntiles = helper ? kJobs : kTiles;
    mbar_spin(afull, 0);
    half_step(0, 0, 0, 0, false);
#pragma unroll 1
    for (int t = 0;; t++) {
      hold = (helper || l == kLayers - 1) && (t + 1 < ntiles);
      PROF(t * 32 + wg * 16 + 0);
#pragma unroll
      for (int s = 0; s < 4; s++) {
        if (s > 0) {
          if (l == 0) mbar_spin(afull + s * 8, fpar);
          PROF(t * 32 + wg * 16 + 8 + s);
          half_step(0, s, 0, t, false);
        }
        retire(0, s, 0, s == 0);
        half_step(0, s, 1, t, s == 0);
        retire(0, s, 1, s == 0);
      }
      if (l == 0) fpar ^= 1;
      PROF(t * 32 + wg * 16 + 1);
#pragma unroll 1
      for (int q = q_second; q < 4; q++) {
#pragma unroll
        for (int s = 0; s < 4; s++) {
          mbar_spin(afull + s * 8, fpar);
          if (s == 0) PROF(t * 32 + wg * 16 + 3 + q);
          half_step(q, s, 0, t, false);
          retire(q, s, 0, false);
          half_step(q, s, 1, t, false);
          retire(q, s, 1, false);
        }
        fpar ^= 1;
      }
      if (t == 0 && !helper) mbar_spin(sb + BAR_BIAS, 0);
      const uint32_t bl = sb + OFF_BIAS + l * 512 + (lane & 3) * 16;
      uint32_t bq[8][4];
      auto load_bias = [&](int U) {
        asm volatile("ld.shared.v4.u32 {%0, %1, %2, %3}, [%4];"
                     : "=r"(bq[U][0]), "=r"(bq[U][1]), "=r"(bq[U][2]), "=r"(bq[U][3]) : "r"(bl + U * 64));
      };
#pragma unroll
      for (int U = 0; U < BPRE; U++) load_bias(U);
      uint32_t fa[4];
#pragma unroll
      for (int g = 0; g < 4; g++) asm volatile("xor.b32 %0, %1, %2;" : "=r"(fa[g]) : "r"(frag0), "r"(g * 32));
      wg_wait<1>();
      release_b(slot_m2);
      if (t + 1 < ntiles) mbar_spin(sb + BAR_BFULL + rb.slot * 8, rb.phase);
      wg_wait<0>();
#pragma unroll
      for (int i = 0; i < 128; i++) asm volatile("" : "+f"(acc[i]) :: "memory");
      release_b(slot_m1);
      if (hold) release_a(3);
      PROF(t * 32 + wg * 16 + 2);

      auto pack = [&](int i) {
        uint32_t v;
        asm("cvt.rn.bf16x2.f32 %0, %1, %2;" : "=r"(v) : "f"(acc[i * 2 + 1]), "f"(acc[i * 2]));
        return v;
      };
      auto cross = [&](int T, int i) {
        uint32_t y, o;
        asm("mul.rn.bf16x2 %0, %1, %2;" : "=r"(y) : "r"(xr[T * 4 + i]), "r"(bq[T >> 1][(T & 1) * 2 + (i >> 1)]));
        asm("fma.rn.bf16x2 %0, %1, %2, %3;" : "=r"(o) : "r"(xr[T * 4 + i]), "r"(pack(T * 4 + i)), "r"(y));
        return o;
      };
      auto reset_acc = [&](int T) {
#pragma unroll
        for (int i = T * 8; i < T * 8 + 8; i += 4)
          asm volatile("ld.volatile.shared.v4.f32 {%0, %1, %2, %3}, [%4];"
                       : "+f"(acc[i]), "+f"(acc[i + 1]), "+f"(acc[i + 2]), "+f"(acc[i + 3]) : "r"(sb + OFF_INIT));
      };
      if (helper) {
        __nv_bfloat16* dst = optr + (size_t)(job_row(t) + (tid >> 5) * 16 + (lane >> 3)) * kDim + j * 256 + (lane & 7) * 8;
        uint64_t pol;
        asm volatile("createpolicy.fractional.L2::evict_first.b64 %0, 1.0;" : "=l"(pol));
#pragma unroll
        for (int T = 0; T < 16; T++) {
          asm volatile("st.global.L2::cache_hint.v4.b32 [%0], {%1, %2, %3, %4}, %5;"
                       ::"l"(dst + (T & 3) * 4 * kDim + (T >> 2) * 64), "r"(pack(T * 4)), "r"(pack(T * 4 + 1)),
                         "r"(pack(T * 4 + 2)), "r"(pack(T * 4 + 3)), "l"(pol) : "memory");
          reset_acc(T);
        }
        asm volatile("bar.sync %0, 128;" ::"r"(wg + 1) : "memory");
        if (wtid == 0) mbar_arrive(sb + BAR_PUB + wg * 8);
      } else if (hold) {
        const bool inject = t + 1 == short_t;
        const uint32_t prow = ((wtid >> 5) * 16 + (lane >> 3)) * 128 + (((lane & 7) ^ (lane >> 3)) << 4);
#pragma unroll
        for (int T = 0; T < 16; T++) {
#pragma unroll
          for (int i = 0; i < 4; i++) xr[T * 4 + i] = cross(T, i);
          if ((T & 1) && (T >> 1) + BPRE < 8) load_bias((T >> 1) + BPRE);
          if ((T & 3) == 3 && !inject) {
#pragma unroll
            for (int g = T - 3; g <= T; g++) reset_acc(g);
          }
          if ((T & 3) == 3 && inject) {
            const int c = T >> 2;
            if (c > 0) mbar_spin(afull + c * 8, fpar);
            else mbar_spin(sb + BAR_EXTRA + wg * 8, 0);
            const uint32_t src = c > 0 ? abase + c * A_SLOT : sb + OFF_EXTRA;
#pragma unroll
            for (int g = 0; g < 4; g++) load_partial(&acc[(c * 4 + g) * 8], src + (prow ^ ((g & 1) * 64)) + g * 512);
            chunk_staged(c);
#pragma unroll
            for (int g = 0; g < 16; g++)
              if ((g >> 2) == c - 1 || (c == 3 && (g >> 2) == 3)) widen_partial(&acc[g * 8]);
            PROF(t * 32 + wg * 16 + 12 + c);
          }
        }
        if (inject) fpar ^= 1;
      } else {
#pragma unroll
        for (int T = 0; T < 16; T++) {
          uint32_t o[4];
#pragma unroll
          for (int i = 0; i < 4; i++) o[i] = cross(T, i);
          stsm4(fa[T & 3] + (T >> 2) * A_SLOT, o);
          if ((T & 3) == 3) chunk_staged(T >> 2);
          if ((T & 1) && (T >> 1) + BPRE < 8) load_bias((T >> 1) + BPRE);
        }
        PROF(t * 32 + wg * 16 + 7);
        fence_async_smem();
        asm volatile("bar.sync %0, 128;" ::"r"(wg + 1) : "memory");
      }
      PROF(t * 32 + wg * 16 + 3);
      if (t + 1 == ntiles) break;
      if (hold) mbar_spin(afull, fpar);
      half_step(0, 0, 0, t, true);
      if (helper || ++l == kLayers) l = 0;
      swap = hold && !helper;
      q_second = (helper || t + 1 == short_t) ? 3 : 1;
      capture_q = -1;
    }
  }
}

__global__ void __launch_bounds__(256) dcn_fallback(const __nv_bfloat16* __restrict__ x0, const __nv_bfloat16* __restrict__ w,
                                                    const __nv_bfloat16* __restrict__ b, __nv_bfloat16* __restrict__ out) {
  __shared__ float xs[8][kDim];
  const size_t r0 = (size_t)blockIdx.x * 8;
  for (int i = threadIdx.x; i < 8 * kDim; i += 256) xs[i / kDim][i % kDim] = __bfloat162float(x0[r0 * kDim + i]);
  __syncthreads();
  for (int l = 0; l < kLayers; l++) {
    float a[4][8] = {};
    for (int k = 0; k < kDim; k++) {
#pragma unroll
      for (int c = 0; c < 4; c++) {
        const float wv = __bfloat162float(w[((size_t)l * kDim + k) * kDim + c * 256 + threadIdx.x]);
#pragma unroll
        for (int r = 0; r < 8; r++) a[c][r] += xs[r][k] * wv;
      }
    }
    __syncthreads();
#pragma unroll
    for (int c = 0; c < 4; c++) {
      const int n = c * 256 + threadIdx.x;
#pragma unroll
      for (int r = 0; r < 8; r++) {
        const float v = __bfloat162float(x0[(r0 + r) * kDim + n]) * (a[c][r] + __bfloat162float(b[l * kDim + n])) + xs[r][n];
        xs[r][n] = __bfloat162float(__float2bfloat16(v));
      }
    }
    __syncthreads();
  }
  for (int i = threadIdx.x; i < 8 * kDim; i += 256) out[r0 * kDim + i] = __float2bfloat16(xs[i / kDim][i % kDim]);
}

typedef CUresult (*EncodeFn)(CUtensorMap*, CUtensorMapDataType, cuuint32_t, void*, const cuuint64_t*, const cuuint64_t*,
                             const cuuint32_t*, const cuuint32_t*, CUtensorMapInterleave, CUtensorMapSwizzle,
                             CUtensorMapL2promotion, CUtensorMapFloatOOBfill);

static void make_map_2d(EncodeFn enc, CUtensorMap* m, void* ptr, uint64_t rows, uint32_t box_rows) {
  cuuint64_t dims[2] = {(cuuint64_t)kDim, rows};
  cuuint64_t strides[1] = {kDim * 2};
  cuuint32_t box[2] = {64, box_rows};
  cuuint32_t es[2] = {1, 1};
  enc(m, CU_TENSOR_MAP_DATA_TYPE_BFLOAT16, 2, ptr, dims, strides, box, es, CU_TENSOR_MAP_INTERLEAVE_NONE,
      CU_TENSOR_MAP_SWIZZLE_128B, CU_TENSOR_MAP_L2_PROMOTION_L2_128B, CU_TENSOR_MAP_FLOAT_OOB_FILL_NONE);
}

}

extern "C" void kernel_launch(void* const* d_in, const int* in_sizes, int n_in, void* d_out, int out_size) {
  using namespace dcn;
  (void)in_sizes; (void)n_in; (void)out_size;
  void* fn = nullptr;
  cudaDriverEntryPointQueryResult qr;
  cudaGetDriverEntryPoint("cuTensorMapEncodeTiled", &fn, cudaEnableDefault, &qr);
  EncodeFn enc = (EncodeFn)fn;
  CUtensorMap mx64, mx32, mo64, mo32, mw;
  make_map_2d(enc, &mx64, d_in[0], kRows, 64);
  make_map_2d(enc, &mx32, d_in[0], kRows, 32);
  make_map_2d(enc, &mo64, d_out, kRows, 64);
  make_map_2d(enc, &mo32, d_out, kRows, 32);
  {
    cuuint64_t dims[3] = {64, (cuuint64_t)kLayers * kDim, kDim / 64};
    cuuint64_t strides[2] = {kDim * 2, 128};
    cuuint32_t box[3] = {64, 32, 4};
    cuuint32_t es[3] = {1, 1, 1};
    enc(&mw, CU_TENSOR_MAP_DATA_TYPE_BFLOAT16, 3, d_in[1], dims, strides, box, es, CU_TENSOR_MAP_INTERLEAVE_NONE,
        CU_TENSOR_MAP_SWIZZLE_128B, CU_TENSOR_MAP_L2_PROMOTION_L2_128B, CU_TENSOR_MAP_FLOAT_OOB_FILL_NONE);
  }
  const __nv_bfloat16* x0 = (const __nv_bfloat16*)d_in[0];
  const __nv_bfloat16* w = (const __nv_bfloat16*)d_in[1];
  const __nv_bfloat16* b = (const __nv_bfloat16*)d_in[2];
  __nv_bfloat16* out = (__nv_bfloat16*)d_out;
  constexpr int smem = SMEM_BYTES + PROF_SMEM;
  cudaFuncSetAttribute(dcn_kernel, cudaFuncAttributeMaxDynamicSharedMemorySize, smem);

  cudaLaunchConfig_t cfg = {};
  cfg.gridDim = dim3(4 * kGroups + 4);
  cfg.blockDim = dim3(384);
  cfg.dynamicSmemBytes = smem;
  cudaLaunchAttribute attr;
  attr.id = cudaLaunchAttributeClusterDimension;
  attr.val.clusterDim.x = 2;
  attr.val.clusterDim.y = 1;
  attr.val.clusterDim.z = 1;
  cfg.attrs = &attr;
  cfg.numAttrs = 1;
  int clusters = 0;
  cudaOccupancyMaxActiveClusters(&clusters, dcn_kernel, &cfg);
  if (clusters >= 2 * kGroups) {
    const int grid = 4 * kGroups + (clusters >= 2 * kGroups + 2 ? 4 : 0);
    dcn_kernel<<<grid, 384, smem>>>(mx64, mx32, mo64, mo32, mw, x0, w, b, out);
  } else {
    dcn_fallback<<<kRows / 8, 256>>>(x0, w, b, out);
  }
}
```

```cpp
#include <cuda_runtime.h>
#include <cuda.h>
#include <cuda_bf16.h>
#include <stdint.h>

namespace dcn {

template <int TA, int TB> __device__ __forceinline__ void wgmma_ss_n256(float (&d)[128], uint64_t da, uint64_t db) {
  asm volatile("{\n.reg .pred p;\nsetp.ne.b32 p, %130, 0;\n"
    "wgmma.mma_async.sync.aligned.m64n256k16.f32.bf16.bf16 "
    "{%0, %1, %2, %3, %4, %5, %6, %7, %8, %9, %10, %11, %12, %13, %14, %15, %16, %17, %18, %19, %20, %21, %22, %23, %24, %25, %26, %27, %28, %29, %30, %31, %32, %33, %34, %35, %36, %37, %38, %39, %40, %41, %42, %43, %44, %45, %46, %47, %48, %49, %50, %51, %52, %53, %54, %55, %56, %57, %58, %59, %60, %61, %62, %63, %64, %65, %66, %67, %68, %69, %70, %71, %72, %73, %74, %75, %76, %77, %78, %79, %80, %81, %82, %83, %84, %85, %86, %87, %88, %89, %90, %91, %92, %93, %94, %95, %96, %97, %98, %99, %100, %101, %102, %103, %104, %105, %106, %107, %108, %109, %110, %111, %112, %113, %114, %115, %116, %117, %118, %119, %120, %121, %122, %123, %124, %125, %126, %127}, "
    "%128, %129, p, 1, 1, %131, %132;\n}\n"
    : "+f"(d[0]), "+f"(d[1]), "+f"(d[2]), "+f"(d[3]), "+f"(d[4]), "+f"(d[5]), "+f"(d[6]), "+f"(d[7]), "+f"(d[8]), "+f"(d[9]), "+f"(d[10]), "+f"(d[11]), "+f"(d[12]), "+f"(d[13]), "+f"(d[14]), "+f"(d[15]), "+f"(d[16]), "+f"(d[17]), "+f"(d[18]), "+f"(d[19]), "+f"(d[20]), "+f"(d[21]), "+f"(d[22]), "+f"(d[23]), "+f"(d[24]), "+f"(d[25]), "+f"(d[26]), "+f"(d[27]), "+f"(d[28]), "+f"(d[29]), "+f"(d[30]), "+f"(d[31]), "+f"(d[32]), "+f"(d[33]), "+f"(d[34]), "+f"(d[35]), "+f"(d[36]), "+f"(d[37]), "+f"(d[38]), "+f"(d[39]), "+f"(d[40]), "+f"(d[41]), "+f"(d[42]), "+f"(d[43]), "+f"(d[44]), "+f"(d[45]), "+f"(d[46]), "+f"(d[47]), "+f"(d[48]), "+f"(d[49]), "+f"(d[50]), "+f"(d[51]), "+f"(d[52]), "+f"(d[53]), "+f"(d[54]), "+f"(d[55]), "+f"(d[56]), "+f"(d[57]), "+f"(d[58]), "+f"(d[59]), "+f"(d[60]), "+f"(d[61]), "+f"(d[62]), "+f"(d[63]), "+f"(d[64]), "+f"(d[65]), "+f"(d[66]), "+f"(d[67]), "+f"(d[68]), "+f"(d[69]), "+f"(d[70]), "+f"(d[71]), "+f"(d[72]), "+f"(d[73]), "+f"(d[74]), "+f"(d[75]), "+f"(d[76]), "+f"(d[77]), "+f"(d[78]), "+f"(d[79]), "+f"(d[80]), "+f"(d[81]), "+f"(d[82]), "+f"(d[83]), "+f"(d[84]), "+f"(d[85]), "+f"(d[86]), "+f"(d[87]), "+f"(d[88]), "+f"(d[89]), "+f"(d[90]), "+f"(d[91]), "+f"(d[92]), "+f"(d[93]), "+f"(d[94]), "+f"(d[95]), "+f"(d[96]), "+f"(d[97]), "+f"(d[98]), "+f"(d[99]), "+f"(d[100]), "+f"(d[101]), "+f"(d[102]), "+f"(d[103]), "+f"(d[104]), "+f"(d[105]), "+f"(d[106]), "+f"(d[107]), "+f"(d[108]), "+f"(d[109]), "+f"(d[110]), "+f"(d[111]), "+f"(d[112]), "+f"(d[113]), "+f"(d[114]), "+f"(d[115]), "+f"(d[116]), "+f"(d[117]), "+f"(d[118]), "+f"(d[119]), "+f"(d[120]), "+f"(d[121]), "+f"(d[122]), "+f"(d[123]), "+f"(d[124]), "+f"(d[125]), "+f"(d[126]), "+f"(d[127])
    : "l"(da), "l"(db), "n"(1), "n"(TA), "n"(TB));
}

constexpr int kDim = 1024;
constexpr int kRows = 16384;
constexpr int kLayers = 6;
constexpr int kGroups = 32;
constexpr int kRounds = kRows / 128 / kGroups;
constexpr int kTiles = kRounds * kLayers;

constexpr float kOffset = 171.f / 256.f;
constexpr int kJobs = kGroups;
constexpr int kEpoch = 32;
constexpr int NA = 4;
constexpr int NB = 9;
constexpr int BPRE = 4;
constexpr int A_SLOT = 8192;
constexpr int B_SLOT = 16384;
constexpr int OFF_B = 0;
constexpr int OFF_A = OFF_B + NB * B_SLOT;
constexpr int OFF_EXTRA = OFF_A + 2 * NA * A_SLOT;
constexpr int OFF_BIAS = OFF_EXTRA + A_SLOT;
constexpr int OFF_BAR = OFF_BIAS + kLayers * 256 * 2;
constexpr int BAR_AFULL = OFF_BAR;
constexpr int BAR_BFULL = OFF_BAR + 64;
constexpr int BAR_ORDER = BAR_BFULL + NB * 8;
constexpr int BAR_XREADY = BAR_ORDER + 8;
constexpr int BAR_PUB = BAR_XREADY + 16;
constexpr int BAR_EXTRA = BAR_PUB + 16;
constexpr int BAR_BEMPTY = OFF_BAR + 3 * 64;
constexpr int BAR_BIAS = BAR_BEMPTY + NB * 8;
constexpr int BAR_AEMPTY = OFF_BAR + 5 * 64;
constexpr int BAR_STAGED = OFF_BAR + 6 * 64;
constexpr int SMEM_BYTES = OFF_BAR + 7 * 64;
static_assert(BAR_EXTRA + 16 == BAR_BEMPTY && NA == 4, "barrier groups");
static_assert(SMEM_BYTES <= 232448, "shared memory budget");

constexpr int kFlagSet = 4 * (kGroups + 1) * 2 * 32;
__device__ unsigned int g_flags[2 * kFlagSet];

__device__ __forceinline__ uint32_t smem_u32(const void* p) { return (uint32_t)__cvta_generic_to_shared(p); }
__device__ __forceinline__ void mbar_init(uint32_t bar, int cnt) {
  asm volatile("mbarrier.init.shared::cta.b64 [%0], %1;" ::"r"(bar), "r"(cnt) : "memory");
}
__device__ __forceinline__ void mbar_arrive(uint32_t bar) {
  asm volatile("mbarrier.arrive.shared::cta.b64 _, [%0];" ::"r"(bar) : "memory");
}
__device__ __forceinline__ uint32_t map_cta(uint32_t addr, uint32_t cta) {
  uint32_t r;
  asm volatile("mapa.shared::cluster.u32 %0, %1, %2;" : "=r"(r) : "r"(addr), "r"(cta));
  return r;
}
__device__ __forceinline__ void mbar_arrive_mapped(uint32_t cluster_addr) {
  asm volatile("mbarrier.arrive.shared::cluster.b64 _, [%0];" ::"r"(cluster_addr) : "memory");
}
__device__ __forceinline__ void mbar_wait(uint32_t bar, uint32_t parity) {
  asm volatile(
      "{\n.reg .pred p;\n.reg .u32 c;\n"
      "mbarrier.try_wait.parity.shared::cta.b64 p, [%0], %1;\n"
      "@p bra DONE;\n"
      "mov.u32 c, 0;\n"
      "LOOP:\n"
      "mbarrier.try_wait.parity.shared::cta.b64 p, [%0], %1;\n"
      "@p bra DONE;\n"
      "add.u32 c, c, 1;\n"
      "setp.lt.u32 p, c, 4194304;\n"
      "@p bra LOOP;\n"
      "trap;\n"
      "DONE:\n}"
      ::"r"(bar), "r"(parity) : "memory");
}
__device__ __forceinline__ void mbar_spin(uint32_t bar, uint32_t parity) {
  asm volatile(
      "{\n.reg .pred p;\n"
      "LOOP:\n"
      "mbarrier.try_wait.parity.shared::cta.b64 p, [%0], %1;\n"
      "@!p bra LOOP;\n}"
      ::"r"(bar), "r"(parity) : "memory");
}
#define ELECT_BEGIN "{\n.reg .pred e;\nelect.sync _|e, 0xffffffff;\n"
template <bool STREAM> __device__ __forceinline__ void expect_load_2d_e(uint32_t dst, const CUtensorMap* m, uint32_t bar, int c0, int c1) {
  if (STREAM) {
    asm volatile(ELECT_BEGIN ".reg .b64 pol;\ncreatepolicy.fractional.L2::evict_first.b64 pol, 1.0;\n"
                 "@e mbarrier.arrive.expect_tx.shared::cta.b64 _, [%2], 8192;\n"
                 "@e cp.async.bulk.tensor.2d.shared::cluster.global.mbarrier::complete_tx::bytes.L2::cache_hint [%0], [%1, {%3, %4}], [%2], pol;\n}"
                 ::"r"(dst), "l"(m), "r"(bar), "r"(c0), "r"(c1) : "memory");
  } else {
    asm volatile(ELECT_BEGIN
                 "@e mbarrier.arrive.expect_tx.shared::cta.b64 _, [%2], 8192;\n"
                 "@e cp.async.bulk.tensor.2d.shared::cluster.global.mbarrier::complete_tx::bytes [%0], [%1, {%3, %4}], [%2];\n}"
                 ::"r"(dst), "l"(m), "r"(bar), "r"(c0), "r"(c1) : "memory");
  }
}
__device__ __forceinline__ void expect_load_2d_mc_e(uint32_t dst, const CUtensorMap* m, uint32_t bar, int c0, int c1) {
  asm volatile(ELECT_BEGIN ".reg .b64 pol;\ncreatepolicy.fractional.L2::evict_first.b64 pol, 1.0;\n"
               "@e mbarrier.arrive.expect_tx.shared::cta.b64 _, [%2], 8192;\n"
               "@e cp.async.bulk.tensor.2d.shared::cluster.global.mbarrier::complete_tx::bytes.multicast::cluster.L2::cache_hint [%0], [%1, {%3, %4}], [%2], %5, pol;\n}"
               ::"r"(dst), "l"(m), "r"(bar), "r"(c0), "r"(c1), "h"((uint16_t)3) : "memory");
}
__device__ __forceinline__ void expect_load_3d_e(uint32_t dst, const CUtensorMap* m, uint32_t bar, int c0, int c1, int c2) {
  asm volatile(ELECT_BEGIN
               "@e mbarrier.arrive.expect_tx.shared::cta.b64 _, [%2], 16384;\n"
               "@e cp.async.bulk.tensor.3d.shared::cluster.global.mbarrier::complete_tx::bytes [%0], [%1, {%3, %4, %5}], [%2];\n}"
               ::"r"(dst), "l"(m), "r"(bar), "r"(c0), "r"(c1), "r"(c2) : "memory");
}
template <bool STREAM> __device__ __forceinline__ void store_2d_e(const CUtensorMap* m, uint32_t src, int c0, int c1) {
  if (STREAM) {
    asm volatile(ELECT_BEGIN ".reg .b64 pol;\ncreatepolicy.fractional.L2::evict_first.b64 pol, 1.0;\n"
                 "@e cp.async.bulk.tensor.2d.global.shared::cta.bulk_group.L2::cache_hint [%0, {%2, %3}], [%1], pol;\n}"
                 ::"l"(m), "r"(src), "r"(c0), "r"(c1) : "memory");
  } else {
    asm volatile(ELECT_BEGIN
                 "@e cp.async.bulk.tensor.2d.global.shared::cta.bulk_group [%0, {%2, %3}], [%1];\n}"
                 ::"l"(m), "r"(src), "r"(c0), "r"(c1) : "memory");
  }
}
__device__ __forceinline__ void prefetch_2d_e(const CUtensorMap* m, int c0, int c1) {
  asm volatile(ELECT_BEGIN
               "@e cp.async.bulk.prefetch.tensor.2d.L2.global [%0, {%1, %2}];\n}"
               ::"l"(m), "r"(c0), "r"(c1) : "memory");
}
__device__ __forceinline__ void prefetch_1d_e(const void* ptr, uint32_t bytes) {
  asm volatile(ELECT_BEGIN
               "@e cp.async.bulk.prefetch.L2.global [%0], %1;\n}"
               ::"l"(ptr), "r"(bytes) : "memory");
}
__device__ __forceinline__ void load_expect_3d_e(uint32_t dst, const CUtensorMap* m, uint32_t bar, int c0, int c1, int c2) {
  asm volatile(ELECT_BEGIN
               "@e cp.async.bulk.tensor.3d.shared::cluster.global.mbarrier::complete_tx::bytes [%0], [%1, {%3, %4, %5}], [%2];\n"
               "@e mbarrier.arrive.expect_tx.shared::cta.b64 _, [%2], 16384;\n}"
               ::"r"(dst), "l"(m), "r"(bar), "r"(c0), "r"(c1), "r"(c2) : "memory");
}
__device__ __forceinline__ void grid_wait() {
  asm volatile("{\n.reg .pred p;\n.reg .u32 a, b;\n.reg .u64 c;\n"
               "mov.u64 c, %%clock64;\ncvt.u32.u64 a, c;\n"
               "EDGE:\n"
               "mov.u64 c, %%clock64;\ncvt.u32.u64 b, c;\n"
               "xor.b32 b, b, a;\n"
               "and.b32 b, b, %0;\n"
               "setp.eq.u32 p, b, 0;\n"
               "@p bra.uni EDGE;\n}" ::"n"(512) : "memory");
}
__device__ __forceinline__ void arrive_mapped_e(uint32_t cluster_addr) {
  asm volatile(ELECT_BEGIN "@e mbarrier.arrive.shared::cluster.b64 _, [%0];\n}" ::"r"(cluster_addr) : "memory");
}
__device__ __forceinline__ void arrive_e(uint32_t bar) {
  asm volatile(ELECT_BEGIN "@e mbarrier.arrive.shared::cta.b64 _, [%0];\n}" ::"r"(bar) : "memory");
}
__device__ __forceinline__ void bulk_commit() { asm volatile("cp.async.bulk.commit_group;" ::: "memory"); }
template <int N> __device__ __forceinline__ void bulk_wait() { asm volatile("cp.async.bulk.wait_group %0;" ::"n"(N) : "memory"); }
__device__ __forceinline__ void wg_fence() { asm volatile("wgmma.fence.sync.aligned;" ::: "memory"); }
__device__ __forceinline__ void wg_commit() { asm volatile("wgmma.commit_group.sync.aligned;" ::: "memory"); }
template <int N> __device__ __forceinline__ void wg_wait() { asm volatile("wgmma.wait_group.sync.aligned %0;" ::"n"(N) : "memory"); }
__device__ __forceinline__ void fence_async_global() { asm volatile("fence.proxy.async.global;" ::: "memory"); }
__device__ __forceinline__ void st_relaxed(unsigned int* p, unsigned int v) {
  asm volatile("st.relaxed.gpu.global.u32 [%0], %1;" ::"l"(p), "r"(v) : "memory");
}
__device__ __forceinline__ unsigned int ld_acquire(const unsigned int* p) {
  unsigned int v;
  asm volatile("ld.acquire.gpu.global.u32 %0, [%1];" : "=r"(v) : "l"(p) : "memory");
  return v;
}
__device__ __forceinline__ void ldsm4(uint32_t* r, uint32_t addr) {
  asm volatile("ldmatrix.sync.aligned.m8n8.x4.shared.b16 {%0, %1, %2, %3}, [%4];"
               : "=r"(r[0]), "=r"(r[1]), "=r"(r[2]), "=r"(r[3]) : "r"(addr) : "memory");
}
__device__ __forceinline__ void stsm4(uint32_t addr, const uint32_t* r) {
  asm volatile("stmatrix.sync.aligned.m8n8.x4.shared.b16 [%0], {%1, %2, %3, %4};"
               ::"r"(addr), "r"(r[0]), "r"(r[1]), "r"(r[2]), "r"(r[3]) : "memory");
}
__device__ __forceinline__ void load_partial(float* a, uint32_t addr) {
  asm volatile("ld.shared.v4.f32 {%0, %1, %2, %3}, [%4];"
               : "+f"(a[4]), "+f"(a[5]), "+f"(a[6]), "+f"(a[7]) : "r"(addr) : "memory");
}
__device__ __forceinline__ void widen_partial(float* a) {
  asm volatile("shl.b32 %0, %4, 16;\nand.b32 %1, %4, 0xffff0000;\n"
               "shl.b32 %2, %5, 16;\nand.b32 %3, %5, 0xffff0000;\n"
               "shl.b32 %4, %6, 16;\nand.b32 %5, %6, 0xffff0000;\n"
               "shl.b32 %6, %7, 16;\nand.b32 %7, %7, 0xffff0000;"
               : "+f"(a[0]), "+f"(a[1]), "+f"(a[2]), "+f"(a[3]), "+f"(a[4]), "+f"(a[5]), "+f"(a[6]), "+f"(a[7]));
}
template <bool V> struct Flag { static constexpr bool value = V; };
__device__ __forceinline__ void fence_async_smem() { asm volatile("fence.proxy.async.shared::cta;" ::: "memory"); }
__device__ __forceinline__ void cluster_arrive_relaxed() { asm volatile("barrier.cluster.arrive.relaxed.aligned;" ::: "memory"); }
__device__ __forceinline__ void cluster_wait() { asm volatile("barrier.cluster.wait.acquire.aligned;" ::: "memory"); }
__device__ __forceinline__ void prefetch_map(const CUtensorMap* m) {
  asm volatile("prefetch.tensormap [%0];" ::"l"(m) : "memory");
}
__device__ __forceinline__ void poll_flag(const unsigned int* ptr, unsigned int target) {
  asm volatile(
      "{\n.reg .pred p;\n.reg .u32 c;\n.reg .s32 v;\n"
      "mov.u32 c, 0;\n"
      "LOOP:\n"
      "ld.acquire.gpu.global.s32 v, [%0];\n"
      "sub.s32 v, v, %1;\n"
      "setp.ge.s32 p, v, 0;\n"
      "@p bra DONE;\n"
      "add.u32 c, c, 1;\n"
      "setp.lt.u32 p, c, 4194304;\n"
      "@p bra LOOP;\n"
      "trap;\n"
      "DONE:\n}"
      ::"l"(ptr), "r"(target) : "memory");
}

constexpr uint32_t DESC_HI = (1024u >> 4) | (1u << 30);
__device__ __forceinline__ uint64_t desc(uint32_t lo) { return ((uint64_t)DESC_HI << 32) | lo; }
constexpr uint32_t DESC_A_LBO = 1u << 16;
constexpr uint32_t DESC_B_LBO = (4096u >> 4) << 16;

struct Ring {
  uint32_t slot, phase;
  template <int N> __device__ __forceinline__ void next() {
    if (++slot == N) { slot = 0; phase ^= 1; }
  }
};

__device__ __forceinline__ int kgroup_col(int j, int q) {
  return q == 0 ? j : (q == 1 ? (j ^ 1) : (((j ^ 2) & ~1) + (q - 2)));
}

__device__ __forceinline__ int role_of_cluster(int c) {
  const int a = c - 4;
  const int b = c - 36, r = (b * 37) >> 8;
  const int first = (a & ~7) + (a & 3) * 2 + ((a >> 2) & 1);
  const int second = 32 + r * 8 + ((0x7531640 >> (((b - r * 7) * 4) & 31)) & 7);
  return c >= 2 * kGroups ? c : (c >= 36 ? second : (c >= 4 ? first : 34 + c * 8));
}
__device__ __forceinline__ int helped_round(int grp) { return (grp & 2) ? (grp & 3) - 1 : 3; }
__device__ __forceinline__ int job_of_group(int grp) {
  return (grp & 2) ? (grp & 1) * 8 + (grp >> 2) : 16 + (grp >> 2) * 2 + (grp & 1);
}
__device__ __forceinline__ int job_row(int n) {
  const int grp = n < 16 ? (n & 7) * 4 + 2 + (n >> 3) : ((n - 16) >> 1) * 4 + (n & 1);
  return (helped_round(grp) * kGroups + grp) * 128;
}

#define PROF_ENDS(idx) do {} while (0)
#define PROF_SVC(idx) do {} while (0)
#define PROF_AT(idx) do {} while (0)
#define PROF_AT_DUMP() do {} while (0)
#define PROF(idx) do {} while (0)
#define PROF_DUMP() do {} while (0)
constexpr int PROF_SMEM = 0;

__global__ void __cluster_dims__(2, 1, 1) __launch_bounds__(384, 1)
dcn_kernel(const __grid_constant__ CUtensorMap mx64, const __grid_constant__ CUtensorMap mx32,
           const __grid_constant__ CUtensorMap mo64, const __grid_constant__ CUtensorMap mo32,
           const __grid_constant__ CUtensorMap mw, const __nv_bfloat16* __restrict__ xptr,
           const __nv_bfloat16* __restrict__ wptr, const __nv_bfloat16* __restrict__ bias, __nv_bfloat16* optr) {
  extern __shared__ __align__(1024) uint8_t smem_raw[];
  const uint32_t sb = smem_u32(smem_raw);
  const int tid = threadIdx.x;
  const __nv_bfloat16 *px = nullptr, *pw = nullptr;
  if (tid < 32) {
    const uint32_t r = blockIdx.x * 32 + tid;
    px = xptr + (size_t)r * kDim;
    pw = wptr + (size_t)((r & 1023) * 64);
    asm volatile("prefetch.global.L2 [%0];" ::"l"(px));
    asm volatile("prefetch.global.L2 [%0];" ::"l"(pw));
    PROF_AT(2);
  }
  if (tid == 256) {
    prefetch_map(&mw);
    prefetch_map(&mx64);
    mbar_init(sb + BAR_BFULL, 1);
    mbar_init(sb + BAR_BFULL + 8, 1);
    mbar_init(sb + BAR_AFULL, 1);
    mbar_init(sb + BAR_AFULL + NA * 8, 1);
    asm volatile("fence.mbarrier_init.release.cluster;" ::: "memory");
  }
  const int wid = __shfl_sync(0xffffffffu, tid >> 5, 0);
  const int bid = role_of_cluster(blockIdx.x >> 1) * 2 + (blockIdx.x & 1);
  const int j = bid & 3;
  const int grp = bid >> 2;
  const bool helper = grp == kGroups;
  const int col0 = helper ? kgroup_col(j, 2) * 256 : 0;
  const int row0 = helper ? job_row(0) : grp * 128;
  auto first_loads = [&](int s) {
    const int col = col0 + s * 64;
    expect_load_3d_e(sb + OFF_B + 2 * s * B_SLOT, &mw, sb + BAR_BFULL + 2 * s * 8, 0, col, j * 4);
    expect_load_2d_e<false>(sb + OFF_A + s * A_SLOT, &mx64, sb + BAR_AFULL + s * 8, col, row0);
    expect_load_2d_e<false>(sb + OFF_A + (NA + s) * A_SLOT, &mx64, sb + BAR_AFULL + (NA + s) * 8, col, row0 + 64);
    expect_load_3d_e(sb + OFF_B + (2 * s + 1) * B_SLOT, &mw, sb + BAR_BFULL + (2 * s + 1) * 8, 0, col + 32, j * 4);
  };
  if (wid == 8) { PROF_AT(0); first_loads(0); PROF_AT(1); }
  __syncthreads();
  const int wg = wid >> 2, warp = wid & 3;
  const uint32_t rank = j & 1;
  const int short_t = (gridDim.x > 4 * kGroups && !helper) ? helped_round(grp) * kLayers : -1;

  if (wg < 2) {
    cluster_arrive_relaxed();
    asm volatile("setmaxnreg.inc.sync.aligned.u32 232;");
    if (tid < 32) asm volatile("prefetch.global.L2 [%0+128];\nprefetch.global.L2 [%1+131072];" ::"l"(px), "l"(pw));
    const int lane = tid & 31;
    const int wtid = tid & 127;
    const uint32_t abase = sb + OFF_A + wg * NA * A_SLOT;
    const uint32_t afull = sb + BAR_AFULL + wg * NA * 8;
    const uint32_t aempty = map_cta(sb + BAR_AEMPTY + wg * NA * 8, wtid == 32 ? (rank ^ 1) : rank);
    const bool rel_a = (wtid == 0) || (wtid == 32);
    const bool rel_b = (wtid == 64);
    const uint32_t frag0 = __shfl_sync(0xffffffffu, abase + ((wtid >> 5) * 16 + ((lane >> 3) & 1) * 8 + (lane & 7)) * 128 +
                                                        (((lane >> 4) ^ (lane & 7)) << 4), lane);
    const uint32_t adesc0 = ((abase & 0x3FFFF) >> 4) | DESC_A_LBO;
    const uint32_t bdesc0 = (((sb + OFF_B) & 0x3FFFF) >> 4) | DESC_B_LBO;

    uint32_t zero;
    asm volatile("mov.u32 %0, %%ctaid.y;" : "=r"(zero));
    float acc[128];
    uint32_t xr[64];
    asm volatile("st.shared.v4.f32 [%0], {%1, %1, %1, %1};" ::"r"(sb + OFF_EXTRA + wid * 16), "f"(kOffset) : "memory");
#pragma unroll
    for (int i = 0; i < 128; i += 4)
      asm volatile("ld.volatile.shared.v4.f32 {%0, %1, %2, %3}, [%4];"
                   : "=f"(acc[i]), "=f"(acc[i + 1]), "=f"(acc[i + 2]), "=f"(acc[i + 3]) : "r"(sb + OFF_EXTRA + wid * 16) : "memory");
#pragma unroll
    for (int i = 0; i < 64; i++) asm volatile("" : "=r"(xr[i]));
    Ring rb{0, 0};
    uint32_t slot_m1 = 0, slot_m2 = 0, slot_m3 = 0;
    uint32_t fpar = 0;
    int l = 0;
    bool hold = false;
    bool swap = false;
    int q_second = helper ? 3 : 1;
    int capture_q = helper ? -1 : j;

    auto release_b = [&](uint32_t slot) {
      if (rel_b) mbar_arrive(sb + BAR_BEMPTY + slot * 8);
    };
    auto release_a = [&](int s) {
      if (rel_a) mbar_arrive_mapped(aempty + s * 8);
    };
    auto chunk_staged = [&](int c) {
      __syncwarp();
      arrive_e(sb + BAR_STAGED + (wg * NA + c) * 8);
    };
    auto capture_slot = [&](int p) {
#pragma unroll
      for (int g = 0; g < 4; g++) ldsm4(&xr[(p * 4 + g) * 4], (frag0 ^ (g * 32)) + p * A_SLOT);
    };
    auto swap_half = [&](int p, int half) {
#pragma unroll
      for (int g = half * 2; g < half * 2 + 2; g++) {
        const uint32_t addr = (frag0 ^ (g * 32)) + p * A_SLOT;
        uint32_t n[4];
        ldsm4(n, addr);
        stsm4(addr, &xr[(p * 4 + g) * 4]);
#pragma unroll
        for (int i = 0; i < 4; i++) xr[(p * 4 + g) * 4 + i] = n[i];
      }
      if (half) chunk_staged(p);
    };
    auto half_step = [&](int q, int s, int h, int t, bool first) {
      if (s == 0 && h == 1 && q == 3 && wg == 1) {
        wg_wait<1>();
        release_b(slot_m2);
        wg_wait<0>();
        release_b(slot_m1);
        if (swap && q_second == 3) { swap_half(3, 0); swap_half(3, 1); }
        release_a(3);
        mbar_spin(sb + BAR_ORDER, t & 1);
      }
      if (!(first && h == 0)) mbar_spin(sb + BAR_BFULL + rb.slot * 8, rb.phase);
      const uint32_t bdesc = bdesc0 + rb.slot * (B_SLOT >> 4);
      const uint32_t adesc = adesc0 + s * (A_SLOT >> 4) + h * 4;
      wg_fence();
      wgmma_ss_n256<0, 1>(acc, desc(adesc), desc(bdesc));
      wgmma_ss_n256<0, 1>(acc, desc(adesc + 2), desc(bdesc + 128));
      wg_commit();
      slot_m3 = slot_m2;
      slot_m2 = slot_m1;
      slot_m1 = rb.slot;
      rb.next<NB>();
      if (s == 3 && h == 1 && q == 3 && wg == 0 && wtid == 96) mbar_arrive(sb + BAR_ORDER);
    };
    auto retire = [&](int q, int s, int h, bool first) {
      if (h == 1 && q == capture_q) capture_slot(s);
      const bool drained = s * 2 + h >= 1 && s * 2 + h <= 2 && q == 3 && wg == 1;
      if (!first && !drained) {
        wg_wait<2>();
        release_b(slot_m3);
        if (h == 1) {
          if (s == 0 || q < 3 || hold) release_a((s + 3) & 3);
          if ((s == 0 || q == 0) && swap && q == (s == 0 ? q_second : 0)) swap_half((s + 3) & 3, 0);
        } else {
          if ((s <= 1) != (q == 0) && swap && q == (s <= 1 ? q_second : 0)) swap_half((s + 2) & 3, 1);
        }
      }
    };

    if (tid < 32) PROF_AT(3);
    cluster_wait();
    if (tid < 32) PROF_AT(4);
    const int ntiles = helper ? kJobs : kTiles;
    mbar_spin(afull, 0);
    if (wtid < 32) PROF_AT(5 + wg);
    half_step(0, 0, 0, 0, false);
    if (wtid < 32) PROF_AT(7 + wg);
#pragma unroll 1
    for (int t = 0;; t++) {
      hold = (helper || l == kLayers - 1) && (t + 1 < ntiles);
      PROF(t * 32 + wg * 16 + 0);
#pragma unroll
      for (int s = 0; s < 4; s++) {
        if (s > 0) {
          if (l == 0) mbar_spin(afull + s * 8, fpar);
          PROF(t * 32 + wg * 16 + 8 + s);
          half_step(0, s, 0, t, false);
        }
        retire(0, s, 0, s == 0);
        half_step(0, s, 1, t, s == 0);
        retire(0, s, 1, s == 0);
      }
      if (l == 0) fpar ^= 1;
      if (t == 0 && wtid < 32) PROF_AT(9 + wg);
      PROF(t * 32 + wg * 16 + 1);
#pragma unroll 1
      for (int q = q_second; q < 4; q++) {
#pragma unroll
        for (int s = 0; s < 4; s++) {
          mbar_spin(afull + s * 8, fpar);
          if (s == 0) PROF(t * 32 + wg * 16 + 3 + q);
          half_step(q, s, 0, t, false);
          retire(q, s, 0, false);
          half_step(q, s, 1, t, false);
          retire(q, s, 1, false);
        }
        fpar ^= 1;
      }
      if (t == 0 && !helper) mbar_spin(sb + BAR_BIAS, 0);
      const uint32_t bl = sb + OFF_BIAS + l * 512 + (lane & 3) * 16;
      uint32_t bq[8][4];
      auto load_bias = [&](int U) {
        asm volatile("ld.shared.v4.u32 {%0, %1, %2, %3}, [%4];"
                     : "=r"(bq[U][0]), "=r"(bq[U][1]), "=r"(bq[U][2]), "=r"(bq[U][3]) : "r"(bl + U * 64));
      };
#pragma unroll
      for (int U = 0; U < BPRE; U++) load_bias(U);
      uint32_t fa[4];
#pragma unroll
      for (int g = 0; g < 4; g++) asm volatile("xor.b32 %0, %1, %2;" : "=r"(fa[g]) : "r"(frag0), "r"(g * 32));
      wg_wait<1>();
      release_b(slot_m2);
      if (t + 1 < ntiles) mbar_spin(sb + BAR_BFULL + rb.slot * 8, rb.phase);
      wg_wait<0>();
#pragma unroll
      for (int i = 0; i < 128; i++) asm volatile("" : "+f"(acc[i]) :: "memory");
      release_b(slot_m1);
      if (hold) release_a(3);
      PROF(t * 32 + wg * 16 + 2);
      if (t == 0 && wtid < 32) PROF_AT(11 + wg);
      if (t == kTiles - 1 && wtid < 32) PROF_AT(13 + wg);

      auto pack = [&](int i) {
        uint32_t v;
        asm("cvt.rn.bf16x2.f32 %0, %1, %2;" : "=r"(v) : "f"(acc[i * 2 + 1]), "f"(acc[i * 2]));
        return v;
      };
      auto cross = [&](int T, int i) {
        uint32_t y, o;
        asm("mul.rn.bf16x2 %0, %1, %2;" : "=r"(y) : "r"(xr[T * 4 + i]), "r"(bq[T >> 1][(T & 1) * 2 + (i >> 1)]));
        asm("fma.rn.bf16x2 %0, %1, %2, %3;" : "=r"(o) : "r"(xr[T * 4 + i]), "r"(pack(T * 4 + i)), "r"(y));
        return o;
      };
      auto reset_acc = [&](int T) {
#pragma unroll
        for (int i = T * 8; i < T * 8 + 8; i++)
          asm("{\n.reg .u32 a, c;\nmov.b32 a, %0;\nmov.b32 c, %2;\nmad.lo.u32 a, a, %1, c;\nmov.b32 %0, a;\n}"
              : "+f"(acc[i]) : "r"(zero), "f"(kOffset));
      };
      if (helper) {
        __nv_bfloat16* dst = optr + (size_t)(job_row(t) + (tid >> 5) * 16 + (lane >> 3)) * kDim + j * 256 + (lane & 7) * 8;
        uint64_t pol;
        asm volatile("createpolicy.fractional.L2::evict_first.b64 %0, 1.0;" : "=l"(pol));
#pragma unroll
        for (int T = 0; T < 16; T++) {
          asm volatile("st.global.L2::cache_hint.v4.b32 [%0], {%1, %2, %3, %4}, %5;"
                       ::"l"(dst + (T & 3) * 4 * kDim + (T >> 2) * 64), "r"(pack(T * 4)), "r"(pack(T * 4 + 1)),
                         "r"(pack(T * 4 + 2)), "r"(pack(T * 4 + 3)), "l"(pol) : "memory");
          reset_acc(T);
        }
        asm volatile("bar.sync %0, 128;" ::"r"(wg + 1) : "memory");
        if (wtid == 0) mbar_arrive(sb + BAR_PUB + wg * 8);
      } else if (hold) {
        const bool inject = t + 1 == short_t;
        const uint32_t prow = ((wtid >> 5) * 16 + (lane >> 3)) * 128 + (((lane & 7) ^ (lane >> 3)) << 4);
#pragma unroll
        for (int T = 0; T < 16; T++) {
#pragma unroll
          for (int i = 0; i < 4; i++) xr[T * 4 + i] = cross(T, i);
          if ((T & 1) && (T >> 1) + BPRE < 8) load_bias((T >> 1) + BPRE);
          if ((T & 3) == 3 && !inject) {
#pragma unroll
            for (int g = T - 3; g <= T; g++) reset_acc(g);
          }
          if ((T & 3) == 3 && inject) {
            const int c = T >> 2;
            if (c > 0) mbar_spin(afull + c * 8, fpar);
            else mbar_spin(sb + BAR_EXTRA + wg * 8, 0);
            const uint32_t src = c > 0 ? abase + c * A_SLOT : sb + OFF_EXTRA;
#pragma unroll
            for (int g = 0; g < 4; g++) load_partial(&acc[(c * 4 + g) * 8], src + (prow ^ ((g & 1) * 64)) + g * 512);
            chunk_staged(c);
#pragma unroll
            for (int g = 0; g < 16; g++)
              if ((g >> 2) == c - 1 || (c == 3 && (g >> 2) == 3)) widen_partial(&acc[g * 8]);
            PROF(t * 32 + wg * 16 + 12 + c);
          }
        }
        if (inject) fpar ^= 1;
      } else {
#pragma unroll
        for (int T = 0; T < 16; T++) {
          uint32_t o[4];
#pragma unroll
          for (int i = 0; i < 4; i++) o[i] = cross(T, i);
          stsm4(fa[T & 3] + (T >> 2) * A_SLOT, o);
          if ((T & 3) == 3) chunk_staged(T >> 2);
          if ((T & 1) && (T >> 1) + BPRE < 8) load_bias((T >> 1) + BPRE);
        }
        PROF(t * 32 + wg * 16 + 7);
        fence_async_smem();
        asm volatile("bar.sync %0, 128;" ::"r"(wg + 1) : "memory");
      }
      PROF(t * 32 + wg * 16 + 3);
      if (t + 1 == ntiles) break;
      if (hold) mbar_spin(afull, fpar);
      half_step(0, 0, 0, t, true);
      if (helper || ++l == kLayers) l = 0;
      swap = hold && !helper;
      q_second = (helper || t + 1 == short_t) ? 3 : 1;
      capture_q = -1;
    }
  } else {
    asm volatile("setmaxnreg.dec.sync.aligned.u32 40;");
    if (tid == 256) {
#pragma unroll
      for (int i = 0; i < 24; i++)
        if (i != 0 && i != NA && i != 8 && i != 9) mbar_init(sb + OFF_BAR + i * 8, 1);
      asm volatile("fence.mbarrier_init.release.cluster;" ::: "memory");
    }
    if (tid == 288) {
#pragma unroll
      for (int i = 0; i <= NB; i++) mbar_init(sb + BAR_BEMPTY + i * 8, 2);
#pragma unroll
      for (int i = 0; i < 2 * NA; i++) { mbar_init(sb + BAR_AEMPTY + i * 8, 2); mbar_init(sb + BAR_STAGED + i * 8, 4); }
      asm volatile("fence.mbarrier_init.release.cluster;" ::: "memory");
    }
    __syncwarp();
    cluster_arrive_relaxed();
#pragma unroll 1
    for (int s = warp == 0 ? 1 : 4; s < 4; s++) first_loads(s);
    if (warp == 0) PROF_AT(15);
    cluster_wait();
    mbar_wait(sb + BAR_AFULL + (warp & 2) * 16, 0);
    if (warp == 0) {
      if (sb & 1023) asm volatile("trap;");
      uint32_t zero;
      asm volatile("mov.u32 %0, %%ctaid.y;" : "=r"(zero));
      const CUtensorMap* mwp = (const CUtensorMap*)((const char*)&mw + zero);
      uint32_t dst = sb + OFF_B + 8 * B_SLOT, bar = sb + BAR_BFULL + 8 * 8, phase = 1;
      int c = 256;
      int mask = helper ? ((j & 2) ^ 2) << 8 : 0;
      int row = c ^ mask;
      int left = helper ? kJobs : kTiles;
#pragma unroll 1
      for (;;) {
        mbar_spin(bar + (BAR_BEMPTY - BAR_BFULL), phase);
        if (c & 512) grid_wait();
        load_expect_3d_e(dst, mwp, bar, zero, row, j * 4);
        c += 32;
        dst += B_SLOT;
        bar += 8;
        if (bar == sb + BAR_BFULL + NB * 8) { bar = sb + BAR_BFULL; dst = sb + OFF_B; phase ^= 1; }
        if ((c & 511) == 0) {
          if ((c & 512) && (helper || kTiles - left == short_t)) c += 512;
          if (c & 512) {
            mask &= 512;
          } else {
            if (--left == 0) break;
            if (helper || c == kLayers * kDim) c = 0;
            if (!helper) mask = j << 8;
          }
        }
        row = c ^ mask;
      }
    } else if (warp <= 2) {
      const int w = warp - 1;
      const uint32_t abase = sb + OFF_A + w * NA * A_SLOT;
      const uint32_t fullb = sb + BAR_AFULL + w * NA * 8;
      const uint32_t emptyb = sb + BAR_AEMPTY + w * NA * 8;
      const uint32_t stagedb = sb + BAR_STAGED + w * NA * 8;
      const unsigned int base = __shfl_sync(0xffffffffu, *(volatile unsigned int*)(g_flags + (bid * 2 + w) * 32), 0);
      uint32_t epar = 0;
      uint32_t spar = 0;
      auto refill = [&](const CUtensorMap* m, int col, int row) {
#pragma unroll 1
        for (int s = 0; s < 4; s++) {
          mbar_wait(emptyb + s * 8, epar);
          expect_load_2d_e<false>(abase + s * A_SLOT, m, fullb + s * 8, col + s * 64, row);
        }
        epar ^= 1;
      };
      auto store_refill = [&](int out_row, int col, int row, bool last_read) {
#pragma unroll 1
        for (int s = 0; s < 4; s++) {
          mbar_wait(stagedb + s * 8, spar);
          fence_async_smem();
          store_2d_e<true>(&mo64, abase + s * A_SLOT, j * 256 + s * 64, out_row);
          bulk_commit();
          bulk_wait<0>();
          __syncwarp();
          mbar_wait(emptyb + s * 8, epar);
          if (last_read) expect_load_2d_e<true>(abase + s * A_SLOT, &mx64, fullb + s * 8, col + s * 64, row);
          else expect_load_2d_e<false>(abase + s * A_SLOT, &mx64, fullb + s * 8, col + s * 64, row);
        }
        spar ^= 1;
        epar ^= 1;
      };
      auto store_tile = [&](auto stream, int out_row) {
#pragma unroll 1
        for (int c = 0; c < 4; c++) {
          mbar_wait(stagedb + c * 8, spar);
          fence_async_smem();
          store_2d_e<decltype(stream)::value>(&mo64, abase + c * A_SLOT, j * 256 + c * 64, out_row);
        }
        spar ^= 1;
        bulk_commit();
        bulk_wait<0>();
        __syncwarp();
      };
      auto refill_shared = [&](const CUtensorMap* m32, int col, int row) {
#pragma unroll 1
        for (int s = 0; s < 4; s++) {
          mbar_wait(emptyb + s * 8, epar);
          expect_load_2d_mc_e(abase + s * A_SLOT + rank * 4096, m32, fullb + s * 8, col + s * 64, row + rank * 32);
        }
        epar ^= 1;
      };
      if (helper) {
#pragma unroll 1
        for (int h = 1; h < 2 * kJobs; h++) refill_shared(&mx32, col0 + (h & 1) * 256, job_row(h >> 1) + w * 64);
      } else {
        const uint32_t xready_peer = map_cta(sb + BAR_XREADY + w * 8, rank ^ 1);
        const unsigned int* oflag = g_flags + ((grp * 4 + kgroup_col(j, 2)) * 2 + w) * 32;
        unsigned int* done_mine = g_flags + kFlagSet + (bid * 2 + w) * 32;
        const unsigned int* done_peer = g_flags + kFlagSet + ((bid ^ 2) * 2 + w) * 32;
        uint32_t nx = 0;
        uint32_t fpar = 0;
#pragma unroll 1
        for (int rd = 0; rd < kRounds; rd++) {
          const int xrow = (rd * kGroups + grp) * 128 + w * 64;
          if (rd == 0) {
            refill(&mx64, 256, xrow);
          } else {
            poll_flag(done_peer, base + nx);
            store_refill(xrow - kGroups * 128, (j ^ 1) * 256, xrow, rd * kLayers == short_t);
          }
          if (rd * kLayers != short_t) {
#pragma unroll 1
            for (int h = 0; h < 2; h++) refill_shared(&mx32, (kgroup_col(rd == 0 ? 0 : j, 2) + h) * 256, xrow);
          }
          fpar ^= 1;
#pragma unroll 1
          for (int l = 1; l < kLayers; l++) {
            if (l > 1) poll_flag(done_peer, base + nx);
            store_tile(Flag<false>(), xrow);
            PROF_SVC((rd * kLayers + l - 1) * 2 + w);
            arrive_mapped_e(xready_peer);
            arrive_e(sb + BAR_PUB + w * 8);
            mbar_wait(sb + BAR_XREADY + w * 8, nx & 1);
            fence_async_global();
            refill(&mo64, (j ^ 1) * 256, xrow);
            if (rd * kLayers + l + 1 == short_t) {
              poll_flag(g_flags + ((4 * kGroups + j) * 2 + 1) * 32, base + job_of_group(grp) + 1);
              fence_async_global();
              if (w == 0) expect_load_2d_e<false>(sb + OFF_EXTRA, &mo64, sb + BAR_EXTRA, j * 256, xrow + kGroups * 128);
            }
#pragma unroll 1
            for (int h = 0; h < 2; h++) {
              poll_flag(oflag + h * 64, base + nx + 1);
              fence_async_global();
              refill_shared(&mo32, (kgroup_col(j, 2) + h) * 256, xrow);
            }
            fpar ^= 1;
            if (rank) {
#pragma unroll 1
              for (int s = 0; s < 4; s++) mbar_wait(fullb + s * 8, fpar);
            }
            nx++;
            if ((tid & 31) == 0) st_relaxed(done_mine, base + (nx == kRounds * (kLayers - 1) ? kEpoch : nx));
            __syncwarp();
          }
          const int nrow = xrow + kGroups * 128;
          if (rd + 1 == kRounds) {
            poll_flag(done_peer, base + nx);
            store_tile(Flag<true>(), xrow);
          } else if ((rd + 1) * kLayers == short_t) {
#pragma unroll 1
            for (int s = 0; s < 4; s++) {
              mbar_wait(emptyb + s * 8, epar);
              if (s == 0) {
                arrive_e(fullb);
                mbar_wait(fullb, fpar ^ 1);
              }
              expect_load_2d_e<false>(abase + s * A_SLOT, s > 0 ? &mo64 : &mx64, fullb + s * 8, j * 256 + s * 64, nrow);
            }
            epar ^= 1;
#pragma unroll 1
            for (int s = 0; s < 4; s++) {
              mbar_wait(stagedb + s * 8, spar);
              fence_async_smem();
              if (s > 0) expect_load_2d_e<false>(abase + s * A_SLOT, &mx64, fullb + s * 8, j * 256 + s * 64, nrow);
              else if (w == 0) expect_load_2d_e<false>(sb + OFF_EXTRA, &mo64, sb + BAR_EXTRA + 8, j * 256, nrow + 64);
            }
            spar ^= 1;
          } else {
            refill(&mx64, j * 256, nrow);
            fpar ^= 1;
          }
          PROF_SVC((rd * kLayers + kLayers - 1) * 2 + w);
        }
      }
    } else {
      const int lane = tid & 31;
      unsigned int* myflag = g_flags + bid * 2 * 32;
      if (lane == 0) { prefetch_map(&mx32); prefetch_map(&mo64); prefetch_map(&mo32); }
      const unsigned int base = *(volatile unsigned int*)myflag;
      auto publish = [&](uint32_t n, uint32_t value) {
#pragma unroll 1
        for (int w = 0; w < 2; w++) {
          mbar_wait(sb + BAR_PUB + w * 8, n & 1);
          asm volatile("fence.acq_rel.gpu;" ::: "memory");
          if (lane == 0) st_relaxed(myflag + w * 32, base + value);
          __syncwarp();
        }
      };
      if (helper) {
#pragma unroll 1
        for (int n = 0; n < kJobs; n++) {
          if (n + 2 < kJobs) {
            const int row = job_row(n + 2);
#pragma unroll 1
            for (int i = 0; i < 8; i++) prefetch_2d_e(&mx64, col0 + rank * 256 + (i & 3) * 64, row + (i >> 2) * 64);
          }
          publish(n, n + 1);
        }
      } else {
        {
          float c[8];
#pragma unroll
          for (int i = 0; i < 8; i++) c[i] = 1.f - kOffset;
#pragma unroll 1
          for (int l = 0; l < kLayers; l++) {
            const uint4 v = *reinterpret_cast<const uint4*>(bias + l * kDim + j * 256 + lane * 8);
            const uint32_t u[4] = {v.x, v.y, v.z, v.w};
#pragma unroll
            for (int i = 0; i < 4; i++) {
              c[2 * i] += __uint_as_float(u[i] << 16);
              c[2 * i + 1] += __uint_as_float(u[i] & 0xffff0000u);
              uint32_t pk;
              asm("cvt.rn.bf16x2.f32 %0, %1, %2;" : "=r"(pk) : "f"(c[2 * i + 1]), "f"(c[2 * i]));
              asm volatile("st.shared.u32 [%0], %1;" ::"r"(sb + OFF_BIAS + l * 512 + (lane >> 2) * 64 + i * 16 + (lane & 3) * 4),
                           "r"(pk) : "memory");
            }
          }
          __syncwarp();
          if (lane < 2) mbar_arrive(sb + BAR_BIAS);
        }
        const __nv_bfloat16* wslice = wptr + bid * 8192;
        prefetch_1d_e(wslice + kDim * kDim, 16384);
        uint32_t nx = 0;
#pragma unroll 1
        for (int rd = 0; rd < kRounds; rd++) {
#pragma unroll 1
          for (int l = 1; l < kLayers; l++) {
            publish(nx, nx + 1 == kRounds * (kLayers - 1) ? kEpoch : nx + 1);
            nx++;
            if (l < kLayers - 1) {
              if (rd == 0) prefetch_1d_e(wslice + (l + 1) * kDim * kDim, 16384);
            } else if (rd + 1 < kRounds) {
              const int nrow = ((rd + 1) * kGroups + grp) * 128;
              bool partial = false;
              if ((rd + 1) * kLayers == short_t) {
                const unsigned int v = ld_acquire(g_flags + ((4 * kGroups + j) * 2 + 1) * 32);
                partial = __shfl_sync(0xffffffffu, (int)(v - (base + job_of_group(grp) + 1)) >= 0, 0);
              }
#pragma unroll 1
              for (int i = partial ? 0 : 8; i < 16; i++) {
                prefetch_2d_e(i < 8 ? &mo64 : &mx64, j * 256 + ((i >> 1) & 3) * 64, nrow + (i & 1) * 64);
                __nanosleep(i < 8 ? 100 : 300);
              }
            }
          }
        }
      }
    }
    if (warp == (helper ? 3 : 2) && (tid & 31) == 0) PROF_ENDS(1002);
    if (warp == 2) { PROF_DUMP(); PROF_AT_DUMP(); }
  }
}

__global__ void __launch_bounds__(256) dcn_fallback(const __nv_bfloat16* __restrict__ x0, const __nv_bfloat16* __restrict__ w,
                                                    const __nv_bfloat16* __restrict__ b, __nv_bfloat16* __restrict__ out) {
  __shared__ float xs[8][kDim];
  const size_t r0 = (size_t)blockIdx.x * 8;
  for (int i = threadIdx.x; i < 8 * kDim; i += 256) xs[i / kDim][i % kDim] = __bfloat162float(x0[r0 * kDim + i]);
  __syncthreads();
  for (int l = 0; l < kLayers; l++) {
    float a[4][8] = {};
    for (int k = 0; k < kDim; k++) {
#pragma unroll
      for (int c = 0; c < 4; c++) {
        const float wv = __bfloat162float(w[((size_t)l * kDim + k) * kDim + c * 256 + threadIdx.x]);
#pragma unroll
        for (int r = 0; r < 8; r++) a[c][r] += xs[r][k] * wv;
      }
    }
    __syncthreads();
#pragma unroll
    for (int c = 0; c < 4; c++) {
      const int n = c * 256 + threadIdx.x;
#pragma unroll
      for (int r = 0; r < 8; r++) {
        const float v = __bfloat162float(x0[(r0 + r) * kDim + n]) * (a[c][r] + __bfloat162float(b[l * kDim + n])) + xs[r][n];
        xs[r][n] = __bfloat162float(__float2bfloat16(v));
      }
    }
    __syncthreads();
  }
  for (int i = threadIdx.x; i < 8 * kDim; i += 256) out[r0 * kDim + i] = __float2bfloat16(xs[i / kDim][i % kDim]);
}

typedef CUresult (*EncodeFn)(CUtensorMap*, CUtensorMapDataType, cuuint32_t, void*, const cuuint64_t*, const cuuint64_t*,
                             const cuuint32_t*, const cuuint32_t*, CUtensorMapInterleave, CUtensorMapSwizzle,
                             CUtensorMapL2promotion, CUtensorMapFloatOOBfill);

static void make_map_2d(EncodeFn enc, CUtensorMap* m, void* ptr, uint64_t rows, uint32_t box_rows) {
  cuuint64_t dims[2] = {(cuuint64_t)kDim, rows};
  cuuint64_t strides[1] = {kDim * 2};
  cuuint32_t box[2] = {64, box_rows};
  cuuint32_t es[2] = {1, 1};
  enc(m, CU_TENSOR_MAP_DATA_TYPE_BFLOAT16, 2, ptr, dims, strides, box, es, CU_TENSOR_MAP_INTERLEAVE_NONE,
      CU_TENSOR_MAP_SWIZZLE_128B, CU_TENSOR_MAP_L2_PROMOTION_L2_128B, CU_TENSOR_MAP_FLOAT_OOB_FILL_NONE);
}

}

extern "C" void kernel_launch(void* const* d_in, const int* in_sizes, int n_in, void* d_out, int out_size) {
  using namespace dcn;
  (void)in_sizes; (void)n_in; (void)out_size;
  void* fn = nullptr;
  cudaDriverEntryPointQueryResult qr;
  cudaGetDriverEntryPoint("cuTensorMapEncodeTiled", &fn, cudaEnableDefault, &qr);
  EncodeFn enc = (EncodeFn)fn;
  CUtensorMap mx64, mx32, mo64, mo32, mw;
  make_map_2d(enc, &mx64, d_in[0], kRows, 64);
  make_map_2d(enc, &mx32, d_in[0], kRows, 32);
  make_map_2d(enc, &mo64, d_out, kRows, 64);
  make_map_2d(enc, &mo32, d_out, kRows, 32);
  {
    cuuint64_t dims[3] = {64, (cuuint64_t)kLayers * kDim, kDim / 64};
    cuuint64_t strides[2] = {kDim * 2, 128};
    cuuint32_t box[3] = {64, 32, 4};
    cuuint32_t es[3] = {1, 1, 1};
    enc(&mw, CU_TENSOR_MAP_DATA_TYPE_BFLOAT16, 3, d_in[1], dims, strides, box, es, CU_TENSOR_MAP_INTERLEAVE_NONE,
        CU_TENSOR_MAP_SWIZZLE_128B, CU_TENSOR_MAP_L2_PROMOTION_L2_128B, CU_TENSOR_MAP_FLOAT_OOB_FILL_NONE);
  }
  const __nv_bfloat16* x0 = (const __nv_bfloat16*)d_in[0];
  const __nv_bfloat16* w = (const __nv_bfloat16*)d_in[1];
  const __nv_bfloat16* b = (const __nv_bfloat16*)d_in[2];
  __nv_bfloat16* out = (__nv_bfloat16*)d_out;
  constexpr int smem = SMEM_BYTES + PROF_SMEM;
  cudaFuncSetAttribute(dcn_kernel, cudaFuncAttributeMaxDynamicSharedMemorySize, smem);

  cudaLaunchConfig_t cfg = {};
  cfg.gridDim = dim3(4 * kGroups + 4);
  cfg.blockDim = dim3(384);
  cfg.dynamicSmemBytes = smem;
  cudaLaunchAttribute attr;
  attr.id = cudaLaunchAttributeClusterDimension;
  attr.val.clusterDim.x = 2;
  attr.val.clusterDim.y = 1;
  attr.val.clusterDim.z = 1;
  cfg.attrs = &attr;
  cfg.numAttrs = 1;
  int clusters = 0;
  cudaOccupancyMaxActiveClusters(&clusters, dcn_kernel, &cfg);
  if (clusters >= 2 * kGroups) {
    const int grid = 4 * kGroups + (clusters >= 2 * kGroups + 2 ? 4 : 0);
    dcn_kernel<<<grid, 384, smem>>>(mx64, mx32, mo64, mo32, mw, x0, w, b, out);
  } else {
    dcn_fallback<<<kRows / 8, 256>>>(x0, w, b, out);
  }
}
```

```cpp
#include <cuda_runtime.h>
#include <cuda.h>
#include <cuda_bf16.h>
#include <stdint.h>

namespace dcn {

template <int TA, int TB> __device__ __forceinline__ void wgmma_ss_n256(float (&d)[128], uint64_t da, uint64_t db) {
  asm volatile("{\n.reg .pred p;\nsetp.ne.b32 p, %130, 0;\n"
    "wgmma.mma_async.sync.aligned.m64n256k16.f32.bf16.bf16 "
    "{%0, %1, %2, %3, %4, %5, %6, %7, %8, %9, %10, %11, %12, %13, %14, %15, %16, %17, %18, %19, %20, %21, %22, %23, %24, %25, %26, %27, %28, %29, %30, %31, %32, %33, %34, %35, %36, %37, %38, %39, %40, %41, %42, %43, %44, %45, %46, %47, %48, %49, %50, %51, %52, %53, %54, %55, %56, %57, %58, %59, %60, %61, %62, %63, %64, %65, %66, %67, %68, %69, %70, %71, %72, %73, %74, %75, %76, %77, %78, %79, %80, %81, %82, %83, %84, %85, %86, %87, %88, %89, %90, %91, %92, %93, %94, %95, %96, %97, %98, %99, %100, %101, %102, %103, %104, %105, %106, %107, %108, %109, %110, %111, %112, %113, %114, %115, %116, %117, %118, %119, %120, %121, %122, %123, %124, %125, %126, %127}, "
    "%128, %129, p, 1, 1, %131, %132;\n}\n"
    : "+f"(d[0]), "+f"(d[1]), "+f"(d[2]), "+f"(d[3]), "+f"(d[4]), "+f"(d[5]), "+f"(d[6]), "+f"(d[7]), "+f"(d[8]), "+f"(d[9]), "+f"(d[10]), "+f"(d[11]), "+f"(d[12]), "+f"(d[13]), "+f"(d[14]), "+f"(d[15]), "+f"(d[16]), "+f"(d[17]), "+f"(d[18]), "+f"(d[19]), "+f"(d[20]), "+f"(d[21]), "+f"(d[22]), "+f"(d[23]), "+f"(d[24]), "+f"(d[25]), "+f"(d[26]), "+f"(d[27]), "+f"(d[28]), "+f"(d[29]), "+f"(d[30]), "+f"(d[31]), "+f"(d[32]), "+f"(d[33]), "+f"(d[34]), "+f"(d[35]), "+f"(d[36]), "+f"(d[37]), "+f"(d[38]), "+f"(d[39]), "+f"(d[40]), "+f"(d[41]), "+f"(d[42]), "+f"(d[43]), "+f"(d[44]), "+f"(d[45]), "+f"(d[46]), "+f"(d[47]), "+f"(d[48]), "+f"(d[49]), "+f"(d[50]), "+f"(d[51]), "+f"(d[52]), "+f"(d[53]), "+f"(d[54]), "+f"(d[55]), "+f"(d[56]), "+f"(d[57]), "+f"(d[58]), "+f"(d[59]), "+f"(d[60]), "+f"(d[61]), "+f"(d[62]), "+f"(d[63]), "+f"(d[64]), "+f"(d[65]), "+f"(d[66]), "+f"(d[67]), "+f"(d[68]), "+f"(d[69]), "+f"(d[70]), "+f"(d[71]), "+f"(d[72]), "+f"(d[73]), "+f"(d[74]), "+f"(d[75]), "+f"(d[76]), "+f"(d[77]), "+f"(d[78]), "+f"(d[79]), "+f"(d[80]), "+f"(d[81]), "+f"(d[82]), "+f"(d[83]), "+f"(d[84]), "+f"(d[85]), "+f"(d[86]), "+f"(d[87]), "+f"(d[88]), "+f"(d[89]), "+f"(d[90]), "+f"(d[91]), "+f"(d[92]), "+f"(d[93]), "+f"(d[94]), "+f"(d[95]), "+f"(d[96]), "+f"(d[97]), "+f"(d[98]), "+f"(d[99]), "+f"(d[100]), "+f"(d[101]), "+f"(d[102]), "+f"(d[103]), "+f"(d[104]), "+f"(d[105]), "+f"(d[106]), "+f"(d[107]), "+f"(d[108]), "+f"(d[109]), "+f"(d[110]), "+f"(d[111]), "+f"(d[112]), "+f"(d[113]), "+f"(d[114]), "+f"(d[115]), "+f"(d[116]), "+f"(d[117]), "+f"(d[118]), "+f"(d[119]), "+f"(d[120]), "+f"(d[121]), "+f"(d[122]), "+f"(d[123]), "+f"(d[124]), "+f"(d[125]), "+f"(d[126]), "+f"(d[127])
    : "l"(da), "l"(db), "n"(1), "n"(TA), "n"(TB));
}

constexpr int kDim = 1024;
constexpr int kRows = 16384;
constexpr int kLayers = 6;
constexpr int kGroups = 32;
constexpr int kRounds = kRows / 128 / kGroups;
constexpr int kTiles = kRounds * kLayers;

constexpr float kOffset = 171.f / 256.f;
constexpr int kJobs = kGroups;
constexpr int kEpoch = 32;
constexpr int NA = 4;
constexpr int NB = 9;
constexpr int BPRE = 4;
constexpr int A_SLOT = 8192;
constexpr int B_SLOT = 16384;
constexpr int OFF_B = 0;
constexpr int OFF_A = OFF_B + NB * B_SLOT;
constexpr int OFF_EXTRA = OFF_A + 2 * NA * A_SLOT;
constexpr int OFF_BIAS = OFF_EXTRA + A_SLOT;
constexpr int OFF_BAR = OFF_BIAS + kLayers * 256 * 2;
constexpr int BAR_AFULL = OFF_BAR;
constexpr int BAR_BFULL = OFF_BAR + 64;
constexpr int BAR_ORDER = BAR_BFULL + NB * 8;
constexpr int BAR_XREADY = BAR_ORDER + 8;
constexpr int BAR_EXTRA = BAR_XREADY + 16;
constexpr int BAR_BEMPTY = OFF_BAR + 3 * 64;
constexpr int BAR_BIAS = BAR_BEMPTY + NB * 8;
constexpr int BAR_PUB = BAR_BIAS + 8;
constexpr int BAR_AEMPTY = OFF_BAR + 5 * 64;
constexpr int BAR_STAGED = OFF_BAR + 6 * 64;
constexpr int SMEM_BYTES = OFF_BAR + 7 * 64;
static_assert(BAR_EXTRA + 16 == OFF_BAR + 22 * 8 && NA == 4, "barrier groups");
static_assert(SMEM_BYTES <= 232448, "shared memory budget");

constexpr int kFlagSet = 4 * (kGroups + 1) * 32;
__device__ unsigned int g_flags[3 * kFlagSet];

__device__ __forceinline__ uint32_t smem_u32(const void* p) { return (uint32_t)__cvta_generic_to_shared(p); }
__device__ __forceinline__ void mbar_init(uint32_t bar, int cnt) {
  asm volatile("mbarrier.init.shared::cta.b64 [%0], %1;" ::"r"(bar), "r"(cnt) : "memory");
}
__device__ __forceinline__ void mbar_arrive(uint32_t bar) {
  asm volatile("mbarrier.arrive.shared::cta.b64 _, [%0];" ::"r"(bar) : "memory");
}
__device__ __forceinline__ uint32_t map_cta(uint32_t addr, uint32_t cta) {
  uint32_t r;
  asm volatile("mapa.shared::cluster.u32 %0, %1, %2;" : "=r"(r) : "r"(addr), "r"(cta));
  return r;
}
__device__ __forceinline__ void mbar_arrive_mapped(uint32_t cluster_addr) {
  asm volatile("mbarrier.arrive.shared::cluster.b64 _, [%0];" ::"r"(cluster_addr) : "memory");
}
__device__ __forceinline__ void mbar_wait(uint32_t bar, uint32_t parity) {
  asm volatile(
      "{\n.reg .pred p;\n.reg .u32 c;\n"
      "mbarrier.try_wait.parity.shared::cta.b64 p, [%0], %1;\n"
      "@p bra DONE;\n"
      "mov.u32 c, 0;\n"
      "LOOP:\n"
      "mbarrier.try_wait.parity.shared::cta.b64 p, [%0], %1;\n"
      "@p bra DONE;\n"
      "add.u32 c, c, 1;\n"
      "setp.lt.u32 p, c, 4194304;\n"
      "@p bra LOOP;\n"
      "trap;\n"
      "DONE:\n}"
      ::"r"(bar), "r"(parity) : "memory");
}
__device__ __forceinline__ void mbar_spin(uint32_t bar, uint32_t parity) {
  asm volatile(
      "{\n.reg .pred p;\n"
      "LOOP:\n"
      "mbarrier.try_wait.parity.shared::cta.b64 p, [%0], %1;\n"
      "@!p bra LOOP;\n}"
      ::"r"(bar), "r"(parity) : "memory");
}
#define ELECT_BEGIN "{\n.reg .pred e;\nelect.sync _|e, 0xffffffff;\n"
template <bool STREAM> __device__ __forceinline__ void expect_load_2d_e(uint32_t dst, const CUtensorMap* m, uint32_t bar, int c0, int c1) {
  if (STREAM) {
    asm volatile(ELECT_BEGIN ".reg .b64 pol;\ncreatepolicy.fractional.L2::evict_first.b64 pol, 1.0;\n"
                 "@e mbarrier.arrive.expect_tx.shared::cta.b64 _, [%2], 8192;\n"
                 "@e cp.async.bulk.tensor.2d.shared::cluster.global.mbarrier::complete_tx::bytes.L2::cache_hint [%0], [%1, {%3, %4}], [%2], pol;\n}"
                 ::"r"(dst), "l"(m), "r"(bar), "r"(c0), "r"(c1) : "memory");
  } else {
    asm volatile(ELECT_BEGIN
                 "@e mbarrier.arrive.expect_tx.shared::cta.b64 _, [%2], 8192;\n"
                 "@e cp.async.bulk.tensor.2d.shared::cluster.global.mbarrier::complete_tx::bytes [%0], [%1, {%3, %4}], [%2];\n}"
                 ::"r"(dst), "l"(m), "r"(bar), "r"(c0), "r"(c1) : "memory");
  }
}
__device__ __forceinline__ void expect_load_2d_mc_e(uint32_t dst, const CUtensorMap* m, uint32_t bar, int c0, int c1) {
  asm volatile(ELECT_BEGIN ".reg .b64 pol;\ncreatepolicy.fractional.L2::evict_first.b64 pol, 1.0;\n"
               "@e mbarrier.arrive.expect_tx.shared::cta.b64 _, [%2], 8192;\n"
               "@e cp.async.bulk.tensor.2d.shared::cluster.global.mbarrier::complete_tx::bytes.multicast::cluster.L2::cache_hint [%0], [%1, {%3, %4}], [%2], %5, pol;\n}"
               ::"r"(dst), "l"(m), "r"(bar), "r"(c0), "r"(c1), "h"((uint16_t)3) : "memory");
}
__device__ __forceinline__ void expect_load_3d_e(uint32_t dst, const CUtensorMap* m, uint32_t bar, int c0, int c1, int c2) {
  asm volatile(ELECT_BEGIN
               "@e mbarrier.arrive.expect_tx.shared::cta.b64 _, [%2], 16384;\n"
               "@e cp.async.bulk.tensor.3d.shared::cluster.global.mbarrier::complete_tx::bytes [%0], [%1, {%3, %4, %5}], [%2];\n}"
               ::"r"(dst), "l"(m), "r"(bar), "r"(c0), "r"(c1), "r"(c2) : "memory");
}
template <bool STREAM> __device__ __forceinline__ void store_2d_e(const CUtensorMap* m, uint32_t src, int c0, int c1) {
  if (STREAM) {
    asm volatile(ELECT_BEGIN ".reg .b64 pol;\ncreatepolicy.fractional.L2::evict_first.b64 pol, 1.0;\n"
                 "@e cp.async.bulk.tensor.2d.global.shared::cta.bulk_group.L2::cache_hint [%0, {%2, %3}], [%1], pol;\n}"
                 ::"l"(m), "r"(src), "r"(c0), "r"(c1) : "memory");
  } else {
    asm volatile(ELECT_BEGIN
                 "@e cp.async.bulk.tensor.2d.global.shared::cta.bulk_group [%0, {%2, %3}], [%1];\n}"
                 ::"l"(m), "r"(src), "r"(c0), "r"(c1) : "memory");
  }
}
__device__ __forceinline__ void prefetch_2d_e(const CUtensorMap* m, int c0, int c1) {
  asm volatile(ELECT_BEGIN
               "@e cp.async.bulk.prefetch.tensor.2d.L2.global [%0, {%1, %2}];\n}"
               ::"l"(m), "r"(c0), "r"(c1) : "memory");
}
__device__ __forceinline__ void prefetch_1d_e(const void* ptr, uint32_t bytes) {
  asm volatile(ELECT_BEGIN
               "@e cp.async.bulk.prefetch.L2.global [%0], %1;\n}"
               ::"l"(ptr), "r"(bytes) : "memory");
}
__device__ __forceinline__ void load_expect_3d_e(uint32_t dst, const CUtensorMap* m, uint32_t bar, int c0, int c1, int c2) {
  asm volatile(ELECT_BEGIN
               "@e cp.async.bulk.tensor.3d.shared::cluster.global.mbarrier::complete_tx::bytes [%0], [%1, {%3, %4, %5}], [%2];\n"
               "@e mbarrier.arrive.expect_tx.shared::cta.b64 _, [%2], 16384;\n}"
               ::"r"(dst), "l"(m), "r"(bar), "r"(c0), "r"(c1), "r"(c2) : "memory");
}
__device__ __forceinline__ void grid_wait() {
  asm volatile("{\n.reg .pred p;\n.reg .u32 a, b;\n.reg .u64 c;\n"
               "mov.u64 c, %%clock64;\ncvt.u32.u64 a, c;\n"
               "EDGE:\n"
               "mov.u64 c, %%clock64;\ncvt.u32.u64 b, c;\n"
               "xor.b32 b, b, a;\n"
               "and.b32 b, b, %0;\n"
               "setp.eq.u32 p, b, 0;\n"
               "@p bra.uni EDGE;\n}" ::"n"(512) : "memory");
}
__device__ __forceinline__ void pace_wait(uint32_t& last, uint32_t gap) {
  asm volatile("{\n.reg .pred p;\n.reg .u32 b, d;\n"
               "AGAIN:\n"
               "mov.u32 b, %%clock;\n"
               "sub.u32 d, b, %0;\n"
               "setp.lt.u32 p, d, %1;\n"
               "@p bra.uni AGAIN;\n"
               "mov.u32 %0, b;\n}" : "+r"(last) : "r"(gap) : "memory");
}
__device__ __forceinline__ void arrive_mapped_e(uint32_t cluster_addr) {
  asm volatile(ELECT_BEGIN "@e mbarrier.arrive.shared::cluster.b64 _, [%0];\n}" ::"r"(cluster_addr) : "memory");
}
__device__ __forceinline__ void arrive_e(uint32_t bar) {
  asm volatile(ELECT_BEGIN "@e mbarrier.arrive.shared::cta.b64 _, [%0];\n}" ::"r"(bar) : "memory");
}
__device__ __forceinline__ void bulk_commit() { asm volatile("cp.async.bulk.commit_group;" ::: "memory"); }
template <int N> __device__ __forceinline__ void bulk_wait() { asm volatile("cp.async.bulk.wait_group %0;" ::"n"(N) : "memory"); }
__device__ __forceinline__ void wg_fence() { asm volatile("wgmma.fence.sync.aligned;" ::: "memory"); }
__device__ __forceinline__ void wg_commit() { asm volatile("wgmma.commit_group.sync.aligned;" ::: "memory"); }
template <int N> __device__ __forceinline__ void wg_wait() { asm volatile("wgmma.wait_group.sync.aligned %0;" ::"n"(N) : "memory"); }
__device__ __forceinline__ void fence_async_global() { asm volatile("fence.proxy.async.global;" ::: "memory"); }
__device__ __forceinline__ void st_relaxed(unsigned int* p, unsigned int v) {
  asm volatile("st.relaxed.gpu.global.u32 [%0], %1;" ::"l"(p), "r"(v) : "memory");
}
__device__ __forceinline__ unsigned int ld_acquire(const unsigned int* p) {
  unsigned int v;
  asm volatile("ld.acquire.gpu.global.u32 %0, [%1];" : "=r"(v) : "l"(p) : "memory");
  return v;
}
__device__ __forceinline__ void ldsm4(uint32_t* r, uint32_t addr) {
  asm volatile("ldmatrix.sync.aligned.m8n8.x4.shared.b16 {%0, %1, %2, %3}, [%4];"
               : "=r"(r[0]), "=r"(r[1]), "=r"(r[2]), "=r"(r[3]) : "r"(addr) : "memory");
}
__device__ __forceinline__ void stsm4(uint32_t addr, const uint32_t* r) {
  asm volatile("stmatrix.sync.aligned.m8n8.x4.shared.b16 [%0], {%1, %2, %3, %4};"
               ::"r"(addr), "r"(r[0]), "r"(r[1]), "r"(r[2]), "r"(r[3]) : "memory");
}
__device__ __forceinline__ void load_partial(float* a, uint32_t addr) {
  asm volatile("ld.shared.v4.f32 {%0, %1, %2, %3}, [%4];"
               : "+f"(a[4]), "+f"(a[5]), "+f"(a[6]), "+f"(a[7]) : "r"(addr) : "memory");
}
__device__ __forceinline__ void widen_partial(float* a) {
  asm volatile("shl.b32 %0, %4, 16;\nand.b32 %1, %4, 0xffff0000;\n"
               "shl.b32 %2, %5, 16;\nand.b32 %3, %5, 0xffff0000;\n"
               "shl.b32 %4, %6, 16;\nand.b32 %5, %6, 0xffff0000;\n"
               "shl.b32 %6, %7, 16;\nand.b32 %7, %7, 0xffff0000;"
               : "+f"(a[0]), "+f"(a[1]), "+f"(a[2]), "+f"(a[3]), "+f"(a[4]), "+f"(a[5]), "+f"(a[6]), "+f"(a[7]));
}
template <bool V> struct Flag { static constexpr bool value = V; };
__device__ __forceinline__ void fence_async_smem() { asm volatile("fence.proxy.async.shared::cta;" ::: "memory"); }
__device__ __forceinline__ void cluster_arrive_relaxed() { asm volatile("barrier.cluster.arrive.relaxed.aligned;" ::: "memory"); }
__device__ __forceinline__ void cluster_wait() { asm volatile("barrier.cluster.wait.acquire.aligned;" ::: "memory"); }
__device__ __forceinline__ void prefetch_map(const CUtensorMap* m) {
  asm volatile("prefetch.tensormap [%0];" ::"l"(m) : "memory");
}
__device__ __forceinline__ void poll_flag(const unsigned int* ptr, unsigned int target) {
  asm volatile(
      "{\n.reg .pred p;\n.reg .u32 c;\n.reg .s32 v;\n"
      "mov.u32 c, 0;\n"
      "LOOP:\n"
      "ld.acquire.gpu.global.s32 v, [%0];\n"
      "sub.s32 v, v, %1;\n"
      "setp.ge.s32 p, v, 0;\n"
      "@p bra DONE;\n"
      "add.u32 c, c, 1;\n"
      "setp.lt.u32 p, c, 4194304;\n"
      "@p bra LOOP;\n"
      "trap;\n"
      "DONE:\n}"
      ::"l"(ptr), "r"(target) : "memory");
}

constexpr uint32_t DESC_HI = (1024u >> 4) | (1u << 30);
__device__ __forceinline__ uint64_t desc(uint32_t lo) { return ((uint64_t)DESC_HI << 32) | lo; }
constexpr uint32_t DESC_A_LBO = 1u << 16;
constexpr uint32_t DESC_B_LBO = (4096u >> 4) << 16;

struct Ring {
  uint32_t slot, phase;
  template <int N> __device__ __forceinline__ void next() {
    if (++slot == N) { slot = 0; phase ^= 1; }
  }
};

__device__ __forceinline__ int kgroup_col(int j, int q) {
  return q == 0 ? j : (q == 1 ? (j ^ 1) : (((j ^ 2) & ~1) + (q - 2)));
}

__device__ __forceinline__ int role_of_cluster(int c) {
  const int a = c - 4;
  const int b = c - 36, r = (b * 37) >> 8;
  const int first = (a & ~7) + (a & 3) * 2 + ((a >> 2) & 1);
  const int second = 32 + r * 8 + ((0x7531640 >> (((b - r * 7) * 4) & 31)) & 7);
  return c >= 2 * kGroups ? c : (c >= 36 ? second : (c >= 4 ? first : 34 + c * 8));
}
__device__ __forceinline__ int helped_round(int grp) { return (grp & 2) ? (grp & 3) - 1 : 3; }
__device__ __forceinline__ int job_of_group(int grp) {
  return (grp & 2) ? (grp & 1) * 8 + (grp >> 2) : 16 + (grp >> 2) * 2 + (grp & 1);
}
__device__ __forceinline__ int job_row(int n) {
  const int grp = n < 16 ? (n & 7) * 4 + 2 + (n >> 3) : ((n - 16) >> 1) * 4 + (n & 1);
  return (helped_round(grp) * kGroups + grp) * 128;
}

#define PROF_START() do {} while (0)
#define PROF_END() do {} while (0)
#define PROF_SVC(idx) do {} while (0)
#define PROF(idx) do {} while (0)
constexpr int PROF_SMEM = 0;

__global__ void __cluster_dims__(2, 1, 1) __launch_bounds__(384, 1)
dcn_kernel(const __grid_constant__ CUtensorMap mx64, const __grid_constant__ CUtensorMap mx32,
           const __grid_constant__ CUtensorMap mo64, const __grid_constant__ CUtensorMap mo32,
           const __grid_constant__ CUtensorMap mw, const __nv_bfloat16* __restrict__ xptr,
           const __nv_bfloat16* __restrict__ wptr, const __nv_bfloat16* __restrict__ bias, __nv_bfloat16* optr) {
  extern __shared__ __align__(1024) uint8_t smem_raw[];
  const uint32_t sb = smem_u32(smem_raw);
  PROF_START();
  const int tid = threadIdx.x;
  const __nv_bfloat16 *px = nullptr, *pw = nullptr;
  if (tid < 32) {
    const uint32_t r = blockIdx.x * 32 + tid;
    px = xptr + (size_t)r * kDim;
    pw = wptr + (size_t)((r & 1023) * 64);
    asm volatile("prefetch.global.L2 [%0];" ::"l"(px));
    asm volatile("prefetch.global.L2 [%0];" ::"l"(pw));
  }
  if (tid == 256) {
    prefetch_map(&mw);
    prefetch_map(&mx64);
    mbar_init(sb + BAR_BFULL, 1);
    mbar_init(sb + BAR_BFULL + 8, 1);
    mbar_init(sb + BAR_AFULL, 1);
    mbar_init(sb + BAR_AFULL + NA * 8, 1);
    asm volatile("fence.mbarrier_init.release.cluster;" ::: "memory");
  }
  const int wid = __shfl_sync(0xffffffffu, tid >> 5, 0);
  const int bid = role_of_cluster(blockIdx.x >> 1) * 2 + (blockIdx.x & 1);
  const int j = bid & 3;
  const int grp = bid >> 2;
  const bool helper = grp == kGroups;
  const int col0 = helper ? kgroup_col(j, 2) * 256 : 0;
  const int row0 = helper ? job_row(0) : grp * 128;
  auto first_loads = [&](int s) {
    const int col = col0 + s * 64;
    expect_load_3d_e(sb + OFF_B + 2 * s * B_SLOT, &mw, sb + BAR_BFULL + 2 * s * 8, 0, col, j * 4);
    expect_load_2d_e<false>(sb + OFF_A + s * A_SLOT, &mx64, sb + BAR_AFULL + s * 8, col, row0);
    expect_load_2d_e<false>(sb + OFF_A + (NA + s) * A_SLOT, &mx64, sb + BAR_AFULL + (NA + s) * 8, col, row0 + 64);
    expect_load_3d_e(sb + OFF_B + (2 * s + 1) * B_SLOT, &mw, sb + BAR_BFULL + (2 * s + 1) * 8, 0, col + 32, j * 4);
  };
  if (wid == 8) first_loads(0);
  __syncthreads();
  const int wg = wid >> 2, warp = wid & 3;
  const uint32_t rank = j & 1;
  const int short_t = (gridDim.x > 4 * kGroups && !helper) ? helped_round(grp) * kLayers : -1;

  if (wg < 2) {
    cluster_arrive_relaxed();
    asm volatile("setmaxnreg.inc.sync.aligned.u32 232;");
    if (tid < 32) asm volatile("prefetch.global.L2 [%0+128];\nprefetch.global.L2 [%1+131072];" ::"l"(px), "l"(pw));
    const int lane = tid & 31;
    const int wtid = tid & 127;
    const uint32_t abase = sb + OFF_A + wg * NA * A_SLOT;
    const uint32_t afull = sb + BAR_AFULL + wg * NA * 8;
    const uint32_t aempty = map_cta(sb + BAR_AEMPTY + wg * NA * 8, wtid == 32 ? (rank ^ 1) : rank);
    const bool rel_a = (wtid == 0) || (wtid == 32);
    const bool rel_b = (wtid == 64);
    const uint32_t frag0 = __shfl_sync(0xffffffffu, abase + ((wtid >> 5) * 16 + ((lane >> 3) & 1) * 8 + (lane & 7)) * 128 +
                                                        (((lane >> 4) ^ (lane & 7)) << 4), lane);
    const uint32_t adesc0 = ((abase & 0x3FFFF) >> 4) | DESC_A_LBO;
    const uint32_t bdesc0 = (((sb + OFF_B) & 0x3FFFF) >> 4) | DESC_B_LBO;

    uint32_t zero;
    asm volatile("mov.u32 %0, %%ctaid.y;" : "=r"(zero));
    float acc[128];
    uint32_t xr[64];
    asm volatile("st.shared.v4.f32 [%0], {%1, %1, %1, %1};" ::"r"(sb + OFF_EXTRA + wid * 16), "f"(kOffset) : "memory");
#pragma unroll
    for (int i = 0; i < 128; i += 4)
      asm volatile("ld.volatile.shared.v4.f32 {%0, %1, %2, %3}, [%4];"
                   : "=f"(acc[i]), "=f"(acc[i + 1]), "=f"(acc[i + 2]), "=f"(acc[i + 3]) : "r"(sb + OFF_EXTRA + wid * 16) : "memory");
#pragma unroll
    for (int i = 0; i < 64; i++) asm volatile("" : "=r"(xr[i]));
    Ring rb{0, 0};
    uint32_t slot_m1 = 0, slot_m2 = 0, slot_m3 = 0;
    uint32_t fpar = 0;
    int l = 0;
    bool hold = false;
    bool swap = false;
    int q_second = helper ? 3 : 1;
    int capture_q = helper ? -1 : j;

    auto release_b = [&](uint32_t slot) {
      if (rel_b) mbar_arrive(sb + BAR_BEMPTY + slot * 8);
    };
    auto release_a = [&](int s) {
      if (rel_a) mbar_arrive_mapped(aempty + s * 8);
    };
    auto chunk_staged = [&](int c) {
      __syncwarp();
      arrive_e(sb + BAR_STAGED + (wg * NA + c) * 8);
    };
    auto capture_slot = [&](int p) {
#pragma unroll
      for (int g = 0; g < 4; g++) ldsm4(&xr[(p * 4 + g) * 4], (frag0 ^ (g * 32)) + p * A_SLOT);
    };
    auto swap_half = [&](int p, int half) {
#pragma unroll
      for (int g = half * 2; g < half * 2 + 2; g++) {
        const uint32_t addr = (frag0 ^ (g * 32)) + p * A_SLOT;
        uint32_t n[4];
        ldsm4(n, addr);
        stsm4(addr, &xr[(p * 4 + g) * 4]);
#pragma unroll
        for (int i = 0; i < 4; i++) xr[(p * 4 + g) * 4 + i] = n[i];
      }
      if (half) chunk_staged(p);
    };
    auto half_step = [&](int q, int s, int h, int t, bool first) {
      if (s == 0 && h == 1 && q == 3 && wg == 1) {
        wg_wait<1>();
        release_b(slot_m2);
        wg_wait<0>();
        release_b(slot_m1);
        if (swap && q_second == 3) { swap_half(3, 0); swap_half(3, 1); }
        release_a(3);
        mbar_spin(sb + BAR_ORDER, t & 1);
      }
      if (!(first && h == 0)) mbar_spin(sb + BAR_BFULL + rb.slot * 8, rb.phase);
      const uint32_t bdesc = bdesc0 + rb.slot * (B_SLOT >> 4);
      const uint32_t adesc = adesc0 + s * (A_SLOT >> 4) + h * 4;
      wg_fence();
      wgmma_ss_n256<0, 1>(acc, desc(adesc), desc(bdesc));
      wgmma_ss_n256<0, 1>(acc, desc(adesc + 2), desc(bdesc + 128));
      wg_commit();
      slot_m3 = slot_m2;
      slot_m2 = slot_m1;
      slot_m1 = rb.slot;
      rb.next<NB>();
      if (s == 3 && h == 1 && q == 3 && wg == 0 && wtid == 96) mbar_arrive(sb + BAR_ORDER);
    };
    auto retire = [&](int q, int s, int h, bool first) {
      if (h == 1 && q == capture_q) capture_slot(s);
      const bool drained = s * 2 + h >= 1 && s * 2 + h <= 2 && q == 3 && wg == 1;
      if (!first && !drained) {
        wg_wait<2>();
        release_b(slot_m3);
        if (h == 1) {
          if (s == 0 || q < 3 || hold) release_a((s + 3) & 3);
          if ((s == 0 || q == 0) && swap && q == (s == 0 ? q_second : 0)) swap_half((s + 3) & 3, 0);
        } else {
          if ((s <= 1) != (q == 0) && swap && q == (s <= 1 ? q_second : 0)) swap_half((s + 2) & 3, 1);
        }
      }
    };

    cluster_wait();
    const int ntiles = helper ? kJobs : kTiles;
    mbar_spin(afull, 0);
    half_step(0, 0, 0, 0, false);
#pragma unroll 1
    for (int t = 0;; t++) {
      hold = (helper || l == kLayers - 1) && (t + 1 < ntiles);
      PROF(t * 32 + wg * 16 + 0);
#pragma unroll
      for (int s = 0; s < 4; s++) {
        if (s > 0) {
          if (l == 0) mbar_spin(afull + s * 8, fpar);
          PROF(t * 32 + wg * 16 + 8 + s);
          half_step(0, s, 0, t, false);
        }
        retire(0, s, 0, s == 0);
        half_step(0, s, 1, t, s == 0);
        retire(0, s, 1, s == 0);
      }
      if (l == 0) fpar ^= 1;
      PROF(t * 32 + wg * 16 + 1);
#pragma unroll 1
      for (int q = q_second; q < 4; q++) {
#pragma unroll
        for (int s = 0; s < 4; s++) {
          mbar_spin(afull + s * 8, fpar);
          if (s == 0) PROF(t * 32 + wg * 16 + 3 + q);
          half_step(q, s, 0, t, false);
          retire(q, s, 0, false);
          half_step(q, s, 1, t, false);
          retire(q, s, 1, false);
        }
        fpar ^= 1;
      }
      if (t == 0 && !helper) mbar_spin(sb + BAR_BIAS, 0);
      const uint32_t bl = sb + OFF_BIAS + l * 512 + (lane & 3) * 16;
      uint32_t bq[8][4];
      auto load_bias = [&](int U) {
        asm volatile("ld.shared.v4.u32 {%0, %1, %2, %3}, [%4];"
                     : "=r"(bq[U][0]), "=r"(bq[U][1]), "=r"(bq[U][2]), "=r"(bq[U][3]) : "r"(bl + U * 64));
      };
#pragma unroll
      for (int U = 0; U < BPRE; U++) load_bias(U);
      uint32_t fa[4];
#pragma unroll
      for (int g = 0; g < 4; g++) asm volatile("xor.b32 %0, %1, %2;" : "=r"(fa[g]) : "r"(frag0), "r"(g * 32));
      wg_wait<1>();
      release_b(slot_m2);
      if (t + 1 < ntiles) mbar_spin(sb + BAR_BFULL + rb.slot * 8, rb.phase);
      wg_wait<0>();
#pragma unroll
      for (int i = 0; i < 128; i++) asm volatile("" : "+f"(acc[i]) :: "memory");
      release_b(slot_m1);
      if (hold) release_a(3);
      PROF(t * 32 + wg * 16 + 2);

      auto pack = [&](int i) {
        uint32_t v;
        asm("cvt.rn.bf16x2.f32 %0, %1, %2;" : "=r"(v) : "f"(acc[i * 2 + 1]), "f"(acc[i * 2]));
        return v;
      };
      auto cross = [&](int T, int i) {
        uint32_t y, o;
        asm("mul.rn.bf16x2 %0, %1, %2;" : "=r"(y) : "r"(xr[T * 4 + i]), "r"(bq[T >> 1][(T & 1) * 2 + (i >> 1)]));
        asm("fma.rn.bf16x2 %0, %1, %2, %3;" : "=r"(o) : "r"(xr[T * 4 + i]), "r"(pack(T * 4 + i)), "r"(y));
        return o;
      };
      auto reset_acc = [&](int T) {
#pragma unroll
        for (int i = T * 8; i < T * 8 + 8; i++)
          asm("{\n.reg .u32 a, c;\nmov.b32 a, %0;\nmov.b32 c, %2;\nmad.lo.u32 a, a, %1, c;\nmov.b32 %0, a;\n}"
              : "+f"(acc[i]) : "r"(zero), "f"(kOffset));
      };
      if (helper) {
        __nv_bfloat16* dst = optr + (size_t)(job_row(t) + (tid >> 5) * 16 + (lane >> 3)) * kDim + j * 256 + (lane & 7) * 8;
        uint64_t pol;
        asm volatile("createpolicy.fractional.L2::evict_first.b64 %0, 1.0;" : "=l"(pol));
#pragma unroll
        for (int T = 0; T < 16; T++) {
          asm volatile("st.global.L2::cache_hint.v4.b32 [%0], {%1, %2, %3, %4}, %5;"
                       ::"l"(dst + (T & 3) * 4 * kDim + (T >> 2) * 64), "r"(pack(T * 4)), "r"(pack(T * 4 + 1)),
                         "r"(pack(T * 4 + 2)), "r"(pack(T * 4 + 3)), "l"(pol) : "memory");
          reset_acc(T);
        }
        asm volatile("bar.sync %0, 128;" ::"r"(wg + 1) : "memory");
        if (wtid == 0) mbar_arrive(sb + BAR_PUB);
      } else if (hold) {
        const bool inject = t + 1 == short_t;
        const uint32_t prow = ((wtid >> 5) * 16 + (lane >> 3)) * 128 + (((lane & 7) ^ (lane >> 3)) << 4);
#pragma unroll
        for (int T = 0; T < 16; T++) {
#pragma unroll
          for (int i = 0; i < 4; i++) xr[T * 4 + i] = cross(T, i);
          if ((T & 1) && (T >> 1) + BPRE < 8) load_bias((T >> 1) + BPRE);
          if ((T & 3) == 3 && !inject) {
#pragma unroll
            for (int g = T - 3; g <= T; g++) reset_acc(g);
          }
          if ((T & 3) == 3 && inject) {
            const int c = T >> 2;
            if (c > 0) mbar_spin(afull + c * 8, fpar);
            else mbar_spin(sb + BAR_EXTRA + wg * 8, 0);
            const uint32_t src = c > 0 ? abase + c * A_SLOT : sb + OFF_EXTRA;
#pragma unroll
            for (int g = 0; g < 4; g++) load_partial(&acc[(c * 4 + g) * 8], src + (prow ^ ((g & 1) * 64)) + g * 512);
            chunk_staged(c);
#pragma unroll
            for (int g = 0; g < 16; g++)
              if ((g >> 2) == c - 1 || (c == 3 && (g >> 2) == 3)) widen_partial(&acc[g * 8]);
            PROF(t * 32 + wg * 16 + 12 + c);
          }
        }
        if (inject) fpar ^= 1;
      } else {
#pragma unroll
        for (int T = 0; T < 16; T++) {
          uint32_t o[4];
#pragma unroll
          for (int i = 0; i < 4; i++) o[i] = cross(T, i);
          stsm4(fa[T & 3] + (T >> 2) * A_SLOT, o);
          if ((T & 3) == 3) chunk_staged(T >> 2);
          if ((T & 1) && (T >> 1) + BPRE < 8) load_bias((T >> 1) + BPRE);
        }
        PROF(t * 32 + wg * 16 + 7);
        fence_async_smem();
        asm volatile("bar.sync %0, 128;" ::"r"(wg + 1) : "memory");
      }
      PROF(t * 32 + wg * 16 + 3);
      if (t + 1 == ntiles) break;
      if (hold) mbar_spin(afull, fpar);
      half_step(0, 0, 0, t, true);
      if (helper || ++l == kLayers) l = 0;
      swap = hold && !helper;
      q_second = (helper || t + 1 == short_t) ? 3 : 1;
      capture_q = -1;
    }
  } else {
    asm volatile("setmaxnreg.dec.sync.aligned.u32 40;");
    if (tid == 256) {
#pragma unroll
      for (int i = 0; i < 22; i++)
        if (i != 0 && i != NA && i != 8 && i != 9) mbar_init(sb + OFF_BAR + i * 8, 1);
      asm volatile("fence.mbarrier_init.release.cluster;" ::: "memory");
    }
    if (tid == 288) {
#pragma unroll
      for (int i = 0; i < NB + 2; i++) mbar_init(sb + BAR_BEMPTY + i * 8, 2);
#pragma unroll
      for (int i = 0; i < 2 * NA; i++) { mbar_init(sb + BAR_AEMPTY + i * 8, 2); mbar_init(sb + BAR_STAGED + i * 8, 4); }
      asm volatile("fence.mbarrier_init.release.cluster;" ::: "memory");
    }
    __syncwarp();
    cluster_arrive_relaxed();
#pragma unroll 1
    for (int s = warp == 0 ? 1 : 4; s < 4; s++) first_loads(s);
    cluster_wait();
    mbar_wait(sb + BAR_AFULL + (warp & 2) * 16, 0);
    if (warp == 0) {
      if (sb & 1023) asm volatile("trap;");
      uint32_t zero;
      asm volatile("mov.u32 %0, %%ctaid.y;" : "=r"(zero));
      const CUtensorMap* mwp = (const CUtensorMap*)((const char*)&mw + zero);
      uint32_t dst = sb + OFF_B + 8 * B_SLOT, bar = sb + BAR_BFULL + 8 * 8, phase = 1;
      int c = 256;
      int mask = helper ? ((j & 2) ^ 2) << 8 : 0;
      int row = c ^ mask;
      int left = helper ? kJobs : kTiles;
#pragma unroll 1
      for (;;) {
        mbar_spin(bar + (BAR_BEMPTY - BAR_BFULL), phase);
        if (c & 512) grid_wait();
        load_expect_3d_e(dst, mwp, bar, zero, row, j * 4);
        c += 32;
        dst += B_SLOT;
        bar += 8;
        if (bar == sb + BAR_BFULL + NB * 8) { bar = sb + BAR_BFULL; dst = sb + OFF_B; phase ^= 1; }
        if ((c & 511) == 0) {
          if ((c & 512) && (helper || kTiles - left == short_t)) c += 512;
          if (c & 512) {
            mask &= 512;
          } else {
            if (--left == 0) break;
            if (helper || c == kLayers * kDim) c = 0;
            if (!helper) mask = j << 8;
          }
        }
        row = c ^ mask;
      }
    } else if (warp <= 2) {
      const int w = warp - 1;
      const uint32_t abase = sb + OFF_A + w * NA * A_SLOT;
      const uint32_t fullb = sb + BAR_AFULL + w * NA * 8;
      const uint32_t emptyb = sb + BAR_AEMPTY + w * NA * 8;
      const uint32_t stagedb = sb + BAR_STAGED + w * NA * 8;
      const unsigned int base = __shfl_sync(0xffffffffu, *(volatile unsigned int*)(g_flags + bid * 32), 0);
      uint32_t epar = 0;
      uint32_t spar = 0;
      uint32_t last = 0;
      auto refill = [&](const CUtensorMap* m, int col, int row) {
#pragma unroll 1
        for (int s = 0; s < 4; s++) {
          mbar_wait(emptyb + s * 8, epar);
          expect_load_2d_e<false>(abase + s * A_SLOT, m, fullb + s * 8, col + s * 64, row);
        }
        epar ^= 1;
      };
      auto store_refill = [&](int out_row, int col, int row, bool last_read) {
#pragma unroll 1
        for (int s = 0; s < 4; s++) {
          mbar_wait(stagedb + s * 8, spar);
          fence_async_smem();
          store_2d_e<true>(&mo64, abase + s * A_SLOT, j * 256 + s * 64, out_row);
          bulk_commit();
          bulk_wait<0>();
          __syncwarp();
          mbar_wait(emptyb + s * 8, epar);
          if (last_read) expect_load_2d_e<true>(abase + s * A_SLOT, &mx64, fullb + s * 8, col + s * 64, row);
          else expect_load_2d_e<false>(abase + s * A_SLOT, &mx64, fullb + s * 8, col + s * 64, row);
        }
        spar ^= 1;
        epar ^= 1;
      };
      auto store_tile = [&](auto stream, int out_row) {
#pragma unroll 1
        for (int c = 0; c < 4; c++) {
          mbar_wait(stagedb + c * 8, spar);
          fence_async_smem();
          if (!decltype(stream)::value) pace_wait(last, w ? 640 : 512);
          store_2d_e<decltype(stream)::value>(&mo64, abase + c * A_SLOT, j * 256 + c * 64, out_row);
        }
        spar ^= 1;
        bulk_commit();
        bulk_wait<0>();
        __syncwarp();
      };
      auto refill_shared = [&](const CUtensorMap* m32, int col, int row) {
#pragma unroll 1
        for (int s = 0; s < 4; s++) {
          mbar_wait(emptyb + s * 8, epar);
          expect_load_2d_mc_e(abase + s * A_SLOT + rank * 4096, m32, fullb + s * 8, col + s * 64, row + rank * 32);
        }
        epar ^= 1;
      };
      if (helper) {
#pragma unroll 1
        for (int h = 1; h < 2 * kJobs; h++) refill_shared(&mx32, col0 + (h & 1) * 256, job_row(h >> 1) + w * 64);
      } else {
        const uint32_t xready_peer = map_cta(sb + BAR_XREADY + w * 8, rank ^ 1);
        const unsigned int* oflag = g_flags + (grp * 4 + kgroup_col(j, 2)) * 32;
        unsigned int* done_mine = g_flags + kFlagSet + (bid * 2 + w) * 32;
        const unsigned int* done_peer = g_flags + kFlagSet + ((bid ^ 2) * 2 + w) * 32;
        uint32_t nx = 0;
        uint32_t fpar = 0;
#pragma unroll 1
        for (int rd = 0; rd < kRounds; rd++) {
          const int xrow = (rd * kGroups + grp) * 128 + w * 64;
          if (rd == 0) {
            refill(&mx64, 256, xrow);
          } else {
            poll_flag(done_peer, base + nx);
            store_refill(xrow - kGroups * 128, (j ^ 1) * 256, xrow, rd * kLayers == short_t);
          }
          if (rd * kLayers != short_t) {
#pragma unroll 1
            for (int h = 0; h < 2; h++) refill_shared(&mx32, (kgroup_col(rd == 0 ? 0 : j, 2) + h) * 256, xrow);
          }
          fpar ^= 1;
#pragma unroll 1
          for (int l = 1; l < kLayers; l++) {
            if (l > 1) poll_flag(done_peer, base + nx);
            store_tile(Flag<false>(), xrow);
            PROF_SVC((rd * kLayers + l - 1) * 2 + w);
            arrive_mapped_e(xready_peer);
            arrive_e(sb + BAR_PUB);
            mbar_wait(sb + BAR_XREADY + w * 8, nx & 1);
            fence_async_global();
            refill(&mo64, (j ^ 1) * 256, xrow);
            if (rd * kLayers + l + 1 == short_t) {
              poll_flag(g_flags + (4 * kGroups + j) * 32, base + job_of_group(grp) + 1);
              fence_async_global();
              if (w == 0) expect_load_2d_e<false>(sb + OFF_EXTRA, &mo64, sb + BAR_EXTRA, j * 256, xrow + kGroups * 128);
            }
#pragma unroll 1
            for (int h = 0; h < 2; h++) {
              poll_flag(oflag + h * 32, base + nx + 1);
              fence_async_global();
              refill_shared(&mo32, (kgroup_col(j, 2) + h) * 256, xrow);
            }
            fpar ^= 1;
            if (rank) {
#pragma unroll 1
              for (int s = 0; s < 4; s++) mbar_wait(fullb + s * 8, fpar);
            }
            nx++;
            if ((tid & 31) == 0) st_relaxed(done_mine, base + (nx == kRounds * (kLayers - 1) ? kEpoch : nx));
            __syncwarp();
          }
          const int nrow = xrow + kGroups * 128;
          if (rd + 1 == kRounds) {
            poll_flag(done_peer, base + nx);
            store_tile(Flag<true>(), xrow);
          } else if ((rd + 1) * kLayers == short_t) {
#pragma unroll 1
            for (int s = 0; s < 4; s++) {
              mbar_wait(emptyb + s * 8, epar);
              if (s == 0) {
                arrive_e(fullb);
                mbar_wait(fullb, fpar ^ 1);
              }
              expect_load_2d_e<false>(abase + s * A_SLOT, s > 0 ? &mo64 : &mx64, fullb + s * 8, j * 256 + s * 64, nrow);
            }
            epar ^= 1;
#pragma unroll 1
            for (int s = 0; s < 4; s++) {
              mbar_wait(stagedb + s * 8, spar);
              fence_async_smem();
              if (s > 0) expect_load_2d_e<false>(abase + s * A_SLOT, &mx64, fullb + s * 8, j * 256 + s * 64, nrow);
              else if (w == 0) expect_load_2d_e<false>(sb + OFF_EXTRA, &mo64, sb + BAR_EXTRA + 8, j * 256, nrow + 64);
            }
            spar ^= 1;
          } else {
            refill(&mx64, j * 256, nrow);
            fpar ^= 1;
          }
          PROF_SVC((rd * kLayers + kLayers - 1) * 2 + w);
        }
      }
    } else {
      const int lane = tid & 31;
      unsigned int* myflag = g_flags + bid * 32;
      if (lane == 0) { prefetch_map(&mx32); prefetch_map(&mo64); prefetch_map(&mo32); }
      const unsigned int base = *(volatile unsigned int*)myflag;
      auto publish = [&](uint32_t n, uint32_t value) {
        mbar_wait(sb + BAR_PUB, n & 1);
        asm volatile("fence.acq_rel.gpu;" ::: "memory");
        if (lane == 0) st_relaxed(myflag, base + value);
        __syncwarp();
      };
      if (helper) {
#pragma unroll 1
        for (int n = 0; n < kJobs; n++) {
          if (n + 2 < kJobs) {
            const int row = job_row(n + 2);
#pragma unroll 1
            for (int i = 0; i < 8; i++) prefetch_2d_e(&mx64, col0 + rank * 256 + (i & 3) * 64, row + (i >> 2) * 64);
          }
          publish(n, n + 1);
        }
      } else {
        {
          float c[8];
#pragma unroll
          for (int i = 0; i < 8; i++) c[i] = 1.f - kOffset;
#pragma unroll 1
          for (int l = 0; l < kLayers; l++) {
            const uint4 v = *reinterpret_cast<const uint4*>(bias + l * kDim + j * 256 + lane * 8);
            const uint32_t u[4] = {v.x, v.y, v.z, v.w};
#pragma unroll
            for (int i = 0; i < 4; i++) {
              c[2 * i] += __uint_as_float(u[i] << 16);
              c[2 * i + 1] += __uint_as_float(u[i] & 0xffff0000u);
              uint32_t pk;
              asm("cvt.rn.bf16x2.f32 %0, %1, %2;" : "=r"(pk) : "f"(c[2 * i + 1]), "f"(c[2 * i]));
              asm volatile("st.shared.u32 [%0], %1;" ::"r"(sb + OFF_BIAS + l * 512 + (lane >> 2) * 64 + i * 16 + (lane & 3) * 4),
                           "r"(pk) : "memory");
            }
          }
          __syncwarp();
          if (lane < 2) mbar_arrive(sb + BAR_BIAS);
        }
        const __nv_bfloat16* wslice = wptr + bid * 8192;
        prefetch_1d_e(wslice + kDim * kDim, 16384);
        uint32_t nx = 0;
#pragma unroll 1
        for (int rd = 0; rd < kRounds; rd++) {
#pragma unroll 1
          for (int l = 1; l < kLayers; l++) {
            publish(nx, nx + 1 == kRounds * (kLayers - 1) ? kEpoch : nx + 1);
            nx++;
            if (l < kLayers - 1) {
              if (rd == 0) prefetch_1d_e(wslice + (l + 1) * kDim * kDim, 16384);
            } else if (rd + 1 < kRounds) {
              const int nrow = ((rd + 1) * kGroups + grp) * 128;
              bool partial = false;
              if ((rd + 1) * kLayers == short_t) {
                const unsigned int v = ld_acquire(g_flags + (4 * kGroups + j) * 32);
                partial = __shfl_sync(0xffffffffu, (int)(v - (base + job_of_group(grp) + 1)) >= 0, 0);
              }
#pragma unroll 1
              for (int i = partial ? 0 : 8; i < 16; i++) {
                prefetch_2d_e(i < 8 ? &mo64 : &mx64, j * 256 + ((i >> 1) & 3) * 64, nrow + (i & 1) * 64);
                __nanosleep(i < 8 ? 100 : 300);
              }
            }
          }
        }
      }
    }
    if (warp == (helper ? 3 : 2)) PROF_END();
  }
}

__global__ void __launch_bounds__(256) dcn_fallback(const __nv_bfloat16* __restrict__ x0, const __nv_bfloat16* __restrict__ w,
                                                    const __nv_bfloat16* __restrict__ b, __nv_bfloat16* __restrict__ out) {
  __shared__ float xs[8][kDim];
  const size_t r0 = (size_t)blockIdx.x * 8;
  for (int i = threadIdx.x; i < 8 * kDim; i += 256) xs[i / kDim][i % kDim] = __bfloat162float(x0[r0 * kDim + i]);
  __syncthreads();
  for (int l = 0; l < kLayers; l++) {
    float a[4][8] = {};
    for (int k = 0; k < kDim; k++) {
#pragma unroll
      for (int c = 0; c < 4; c++) {
        const float wv = __bfloat162float(w[((size_t)l * kDim + k) * kDim + c * 256 + threadIdx.x]);
#pragma unroll
        for (int r = 0; r < 8; r++) a[c][r] += xs[r][k] * wv;
      }
    }
    __syncthreads();
#pragma unroll
    for (int c = 0; c < 4; c++) {
      const int n = c * 256 + threadIdx.x;
#pragma unroll
      for (int r = 0; r < 8; r++) {
        const float v = __bfloat162float(x0[(r0 + r) * kDim + n]) * (a[c][r] + __bfloat162float(b[l * kDim + n])) + xs[r][n];
        xs[r][n] = __bfloat162float(__float2bfloat16(v));
      }
    }
    __syncthreads();
  }
  for (int i = threadIdx.x; i < 8 * kDim; i += 256) out[r0 * kDim + i] = __float2bfloat16(xs[i / kDim][i % kDim]);
}

typedef CUresult (*EncodeFn)(CUtensorMap*, CUtensorMapDataType, cuuint32_t, void*, const cuuint64_t*, const cuuint64_t*,
                             const cuuint32_t*, const cuuint32_t*, CUtensorMapInterleave, CUtensorMapSwizzle,
                             CUtensorMapL2promotion, CUtensorMapFloatOOBfill);

static void make_map_2d(EncodeFn enc, CUtensorMap* m, void* ptr, uint64_t rows, uint32_t box_rows) {
  cuuint64_t dims[2] = {(cuuint64_t)kDim, rows};
  cuuint64_t strides[1] = {kDim * 2};
  cuuint32_t box[2] = {64, box_rows};
  cuuint32_t es[2] = {1, 1};
  enc(m, CU_TENSOR_MAP_DATA_TYPE_BFLOAT16, 2, ptr, dims, strides, box, es, CU_TENSOR_MAP_INTERLEAVE_NONE,
      CU_TENSOR_MAP_SWIZZLE_128B, CU_TENSOR_MAP_L2_PROMOTION_L2_128B, CU_TENSOR_MAP_FLOAT_OOB_FILL_NONE);
}

}

extern "C" void kernel_launch(void* const* d_in, const int* in_sizes, int n_in, void* d_out, int out_size) {
  using namespace dcn;
  (void)in_sizes; (void)n_in; (void)out_size;
  void* fn = nullptr;
  cudaDriverEntryPointQueryResult qr;
  cudaGetDriverEntryPoint("cuTensorMapEncodeTiled", &fn, cudaEnableDefault, &qr);
  EncodeFn enc = (EncodeFn)fn;
  CUtensorMap mx64, mx32, mo64, mo32, mw;
  make_map_2d(enc, &mx64, d_in[0], kRows, 64);
  make_map_2d(enc, &mx32, d_in[0], kRows, 32);
  make_map_2d(enc, &mo64, d_out, kRows, 64);
  make_map_2d(enc, &mo32, d_out, kRows, 32);
  {
    cuuint64_t dims[3] = {64, (cuuint64_t)kLayers * kDim, kDim / 64};
    cuuint64_t strides[2] = {kDim * 2, 128};
    cuuint32_t box[3] = {64, 32, 4};
    cuuint32_t es[3] = {1, 1, 1};
    enc(&mw, CU_TENSOR_MAP_DATA_TYPE_BFLOAT16, 3, d_in[1], dims, strides, box, es, CU_TENSOR_MAP_INTERLEAVE_NONE,
        CU_TENSOR_MAP_SWIZZLE_128B, CU_TENSOR_MAP_L2_PROMOTION_L2_128B, CU_TENSOR_MAP_FLOAT_OOB_FILL_NONE);
  }
  const __nv_bfloat16* x0 = (const __nv_bfloat16*)d_in[0];
  const __nv_bfloat16* w = (const __nv_bfloat16*)d_in[1];
  const __nv_bfloat16* b = (const __nv_bfloat16*)d_in[2];
  __nv_bfloat16* out = (__nv_bfloat16*)d_out;
  constexpr int smem = SMEM_BYTES + PROF_SMEM;
  cudaFuncSetAttribute(dcn_kernel, cudaFuncAttributeMaxDynamicSharedMemorySize, smem);

  cudaLaunchConfig_t cfg = {};
  cfg.gridDim = dim3(4 * kGroups + 4);
  cfg.blockDim = dim3(384);
  cfg.dynamicSmemBytes = smem;
  cudaLaunchAttribute attr;
  attr.id = cudaLaunchAttributeClusterDimension;
  attr.val.clusterDim.x = 2;
  attr.val.clusterDim.y = 1;
  attr.val.clusterDim.z = 1;
  cfg.attrs = &attr;
  cfg.numAttrs = 1;
  int clusters = 0;
  cudaOccupancyMaxActiveClusters(&clusters, dcn_kernel, &cfg);
  if (clusters >= 2 * kGroups) {
    const int grid = 4 * kGroups + (clusters >= 2 * kGroups + 2 ? 4 : 0);
    dcn_kernel<<<grid, 384, smem>>>(mx64, mx32, mo64, mo32, mw, x0, w, b, out);
  } else {
    dcn_fallback<<<kRows / 8, 256>>>(x0, w, b, out);
  }
}
```

```cpp
#include <cuda_runtime.h>
#include <cuda.h>
#include <cuda_bf16.h>
#include <stdint.h>

namespace dcn {

template <int TA, int TB> __device__ __forceinline__ void wgmma_ss_n256(float (&d)[128], uint64_t da, uint64_t db) {
  asm volatile("{\n.reg .pred p;\nsetp.ne.b32 p, %130, 0;\n"
    "wgmma.mma_async.sync.aligned.m64n256k16.f32.bf16.bf16 "
    "{%0, %1, %2, %3, %4, %5, %6, %7, %8, %9, %10, %11, %12, %13, %14, %15, %16, %17, %18, %19, %20, %21, %22, %23, %24, %25, %26, %27, %28, %29, %30, %31, %32, %33, %34, %35, %36, %37, %38, %39, %40, %41, %42, %43, %44, %45, %46, %47, %48, %49, %50, %51, %52, %53, %54, %55, %56, %57, %58, %59, %60, %61, %62, %63, %64, %65, %66, %67, %68, %69, %70, %71, %72, %73, %74, %75, %76, %77, %78, %79, %80, %81, %82, %83, %84, %85, %86, %87, %88, %89, %90, %91, %92, %93, %94, %95, %96, %97, %98, %99, %100, %101, %102, %103, %104, %105, %106, %107, %108, %109, %110, %111, %112, %113, %114, %115, %116, %117, %118, %119, %120, %121, %122, %123, %124, %125, %126, %127}, "
    "%128, %129, p, 1, 1, %131, %132;\n}\n"
    : "+f"(d[0]), "+f"(d[1]), "+f"(d[2]), "+f"(d[3]), "+f"(d[4]), "+f"(d[5]), "+f"(d[6]), "+f"(d[7]), "+f"(d[8]), "+f"(d[9]), "+f"(d[10]), "+f"(d[11]), "+f"(d[12]), "+f"(d[13]), "+f"(d[14]), "+f"(d[15]), "+f"(d[16]), "+f"(d[17]), "+f"(d[18]), "+f"(d[19]), "+f"(d[20]), "+f"(d[21]), "+f"(d[22]), "+f"(d[23]), "+f"(d[24]), "+f"(d[25]), "+f"(d[26]), "+f"(d[27]), "+f"(d[28]), "+f"(d[29]), "+f"(d[30]), "+f"(d[31]), "+f"(d[32]), "+f"(d[33]), "+f"(d[34]), "+f"(d[35]), "+f"(d[36]), "+f"(d[37]), "+f"(d[38]), "+f"(d[39]), "+f"(d[40]), "+f"(d[41]), "+f"(d[42]), "+f"(d[43]), "+f"(d[44]), "+f"(d[45]), "+f"(d[46]), "+f"(d[47]), "+f"(d[48]), "+f"(d[49]), "+f"(d[50]), "+f"(d[51]), "+f"(d[52]), "+f"(d[53]), "+f"(d[54]), "+f"(d[55]), "+f"(d[56]), "+f"(d[57]), "+f"(d[58]), "+f"(d[59]), "+f"(d[60]), "+f"(d[61]), "+f"(d[62]), "+f"(d[63]), "+f"(d[64]), "+f"(d[65]), "+f"(d[66]), "+f"(d[67]), "+f"(d[68]), "+f"(d[69]), "+f"(d[70]), "+f"(d[71]), "+f"(d[72]), "+f"(d[73]), "+f"(d[74]), "+f"(d[75]), "+f"(d[76]), "+f"(d[77]), "+f"(d[78]), "+f"(d[79]), "+f"(d[80]), "+f"(d[81]), "+f"(d[82]), "+f"(d[83]), "+f"(d[84]), "+f"(d[85]), "+f"(d[86]), "+f"(d[87]), "+f"(d[88]), "+f"(d[89]), "+f"(d[90]), "+f"(d[91]), "+f"(d[92]), "+f"(d[93]), "+f"(d[94]), "+f"(d[95]), "+f"(d[96]), "+f"(d[97]), "+f"(d[98]), "+f"(d[99]), "+f"(d[100]), "+f"(d[101]), "+f"(d[102]), "+f"(d[103]), "+f"(d[104]), "+f"(d[105]), "+f"(d[106]), "+f"(d[107]), "+f"(d[108]), "+f"(d[109]), "+f"(d[110]), "+f"(d[111]), "+f"(d[112]), "+f"(d[113]), "+f"(d[114]), "+f"(d[115]), "+f"(d[116]), "+f"(d[117]), "+f"(d[118]), "+f"(d[119]), "+f"(d[120]), "+f"(d[121]), "+f"(d[122]), "+f"(d[123]), "+f"(d[124]), "+f"(d[125]), "+f"(d[126]), "+f"(d[127])
    : "l"(da), "l"(db), "n"(1), "n"(TA), "n"(TB));
}

constexpr int kDim = 1024;
constexpr int kRows = 16384;
constexpr int kLayers = 6;
constexpr int kGroups = 32;
constexpr int kRounds = kRows / 128 / kGroups;
constexpr int kTiles = kRounds * kLayers;

constexpr float kOffset = 171.f / 128.f;
constexpr int kJobs = kGroups;
constexpr int kEpoch = 32;
constexpr int NA = 4;
constexpr int NB = 9;
constexpr int BPRE = 4;
constexpr int NT = 11;
constexpr int A_SLOT = 8192;
constexpr int B_SLOT = 16384;
constexpr int OFF_B = 0;
constexpr int OFF_A = OFF_B + NB * B_SLOT;
constexpr int OFF_EXTRA = OFF_A + 2 * NA * A_SLOT;
constexpr int OFF_BIAS = OFF_EXTRA + A_SLOT;
constexpr int OFF_BAR = OFF_BIAS + kLayers * 256 * 2;
constexpr int BAR_AFULL = OFF_BAR;
constexpr int BAR_BFULL = OFF_BAR + 64;
constexpr int BAR_ORDER = BAR_BFULL + NB * 8;
constexpr int BAR_XREADY = BAR_ORDER + 8;
constexpr int BAR_EXTRA = BAR_XREADY + 16;
constexpr int BAR_BEMPTY = OFF_BAR + 3 * 64;
constexpr int BAR_BIAS = BAR_BEMPTY + NB * 8;
constexpr int BAR_PUB = BAR_BIAS + 8;
constexpr int BAR_AEMPTY = OFF_BAR + 5 * 64;
constexpr int BAR_STAGED = OFF_BAR + 6 * 64;
constexpr int SMEM_BYTES = OFF_BAR + 7 * 64;
static_assert(BAR_EXTRA + 16 == OFF_BAR + 22 * 8 && NA == 4, "barrier groups");
static_assert(SMEM_BYTES <= 232448, "shared memory budget");

constexpr int kFlagSet = 4 * (kGroups + 1) * 32;
__device__ unsigned int g_flags[3 * kFlagSet];

__device__ __forceinline__ uint32_t smem_u32(const void* p) { return (uint32_t)__cvta_generic_to_shared(p); }
__device__ __forceinline__ void mbar_init(uint32_t bar, int cnt) {
  asm volatile("mbarrier.init.shared::cta.b64 [%0], %1;" ::"r"(bar), "r"(cnt) : "memory");
}
__device__ __forceinline__ void mbar_arrive(uint32_t bar) {
  asm volatile("mbarrier.arrive.shared::cta.b64 _, [%0];" ::"r"(bar) : "memory");
}
__device__ __forceinline__ uint32_t map_cta(uint32_t addr, uint32_t cta) {
  uint32_t r;
  asm volatile("mapa.shared::cluster.u32 %0, %1, %2;" : "=r"(r) : "r"(addr), "r"(cta));
  return r;
}
__device__ __forceinline__ void mbar_arrive_mapped(uint32_t cluster_addr) {
  asm volatile("mbarrier.arrive.shared::cluster.b64 _, [%0];" ::"r"(cluster_addr) : "memory");
}
__device__ __forceinline__ void mbar_wait(uint32_t bar, uint32_t parity) {
  asm volatile(
      "{\n.reg .pred p;\n.reg .u32 c;\n"
      "mbarrier.try_wait.parity.shared::cta.b64 p, [%0], %1;\n"
      "@p bra DONE;\n"
      "mov.u32 c, 0;\n"
      "LOOP:\n"
      "mbarrier.try_wait.parity.shared::cta.b64 p, [%0], %1;\n"
      "@p bra DONE;\n"
      "add.u32 c, c, 1;\n"
      "setp.lt.u32 p, c, 4194304;\n"
      "@p bra LOOP;\n"
      "trap;\n"
      "DONE:\n}"
      ::"r"(bar), "r"(parity) : "memory");
}
__device__ __forceinline__ void mbar_spin(uint32_t bar, uint32_t parity) {
  asm volatile(
      "{\n.reg .pred p;\n"
      "LOOP:\n"
      "mbarrier.try_wait.parity.shared::cta.b64 p, [%0], %1;\n"
      "@!p bra LOOP;\n}"
      ::"r"(bar), "r"(parity) : "memory");
}
#define ELECT_BEGIN "{\n.reg .pred e;\nelect.sync _|e, 0xffffffff;\n"
template <bool STREAM> __device__ __forceinline__ void expect_load_2d_e(uint32_t dst, const CUtensorMap* m, uint32_t bar, int c0, int c1) {
  if (STREAM) {
    asm volatile(ELECT_BEGIN ".reg .b64 pol;\ncreatepolicy.fractional.L2::evict_first.b64 pol, 1.0;\n"
                 "@e mbarrier.arrive.expect_tx.shared::cta.b64 _, [%2], 8192;\n"
                 "@e cp.async.bulk.tensor.2d.shared::cluster.global.mbarrier::complete_tx::bytes.L2::cache_hint [%0], [%1, {%3, %4}], [%2], pol;\n}"
                 ::"r"(dst), "l"(m), "r"(bar), "r"(c0), "r"(c1) : "memory");
  } else {
    asm volatile(ELECT_BEGIN
                 "@e mbarrier.arrive.expect_tx.shared::cta.b64 _, [%2], 8192;\n"
                 "@e cp.async.bulk.tensor.2d.shared::cluster.global.mbarrier::complete_tx::bytes [%0], [%1, {%3, %4}], [%2];\n}"
                 ::"r"(dst), "l"(m), "r"(bar), "r"(c0), "r"(c1) : "memory");
  }
}
__device__ __forceinline__ void expect_load_2d_mc_e(uint32_t dst, const CUtensorMap* m, uint32_t bar, int c0, int c1) {
  asm volatile(ELECT_BEGIN ".reg .b64 pol;\ncreatepolicy.fractional.L2::evict_first.b64 pol, 1.0;\n"
               "@e mbarrier.arrive.expect_tx.shared::cta.b64 _, [%2], 8192;\n"
               "@e cp.async.bulk.tensor.2d.shared::cluster.global.mbarrier::complete_tx::bytes.multicast::cluster.L2::cache_hint [%0], [%1, {%3, %4}], [%2], %5, pol;\n}"
               ::"r"(dst), "l"(m), "r"(bar), "r"(c0), "r"(c1), "h"((uint16_t)3) : "memory");
}
__device__ __forceinline__ void expect_load_3d_e(uint32_t dst, const CUtensorMap* m, uint32_t bar, int c0, int c1, int c2) {
  asm volatile(ELECT_BEGIN
               "@e mbarrier.arrive.expect_tx.shared::cta.b64 _, [%2], 16384;\n"
               "@e cp.async.bulk.tensor.3d.shared::cluster.global.mbarrier::complete_tx::bytes [%0], [%1, {%3, %4, %5}], [%2];\n}"
               ::"r"(dst), "l"(m), "r"(bar), "r"(c0), "r"(c1), "r"(c2) : "memory");
}
template <bool STREAM> __device__ __forceinline__ void store_2d_e(const CUtensorMap* m, uint32_t src, int c0, int c1) {
  if (STREAM) {
    asm volatile(ELECT_BEGIN ".reg .b64 pol;\ncreatepolicy.fractional.L2::evict_first.b64 pol, 1.0;\n"
                 "@e cp.async.bulk.tensor.2d.global.shared::cta.bulk_group.L2::cache_hint [%0, {%2, %3}], [%1], pol;\n}"
                 ::"l"(m), "r"(src), "r"(c0), "r"(c1) : "memory");
  } else {
    asm volatile(ELECT_BEGIN
                 "@e cp.async.bulk.tensor.2d.global.shared::cta.bulk_group [%0, {%2, %3}], [%1];\n}"
                 ::"l"(m), "r"(src), "r"(c0), "r"(c1) : "memory");
  }
}
__device__ __forceinline__ void prefetch_2d_e(const CUtensorMap* m, int c0, int c1) {
  asm volatile(ELECT_BEGIN
               "@e cp.async.bulk.prefetch.tensor.2d.L2.global [%0, {%1, %2}];\n}"
               ::"l"(m), "r"(c0), "r"(c1) : "memory");
}
__device__ __forceinline__ void prefetch_1d_e(const void* ptr, uint32_t bytes) {
  asm volatile(ELECT_BEGIN
               "@e cp.async.bulk.prefetch.L2.global [%0], %1;\n}"
               ::"l"(ptr), "r"(bytes) : "memory");
}
__device__ __forceinline__ void load_expect_3d_e(uint32_t dst, const CUtensorMap* m, uint32_t bar, int c0, int c1, int c2) {
  asm volatile(ELECT_BEGIN
               "@e cp.async.bulk.tensor.3d.shared::cluster.global.mbarrier::complete_tx::bytes [%0], [%1, {%3, %4, %5}], [%2];\n"
               "@e mbarrier.arrive.expect_tx.shared::cta.b64 _, [%2], 16384;\n}"
               ::"r"(dst), "l"(m), "r"(bar), "r"(c0), "r"(c1), "r"(c2) : "memory");
}
__device__ __forceinline__ void pace_wait(uint32_t& last, uint32_t gap) {
  asm volatile("{\n.reg .pred p;\n.reg .u32 b, d;\n"
               "AGAIN:\n"
               "mov.u32 b, %%clock;\n"
               "sub.u32 d, b, %0;\n"
               "setp.lt.u32 p, d, %1;\n"
               "@p bra.uni AGAIN;\n"
               "mov.u32 %0, b;\n}" : "+r"(last) : "r"(gap) : "memory");
}
__device__ __forceinline__ void arrive_mapped_e(uint32_t cluster_addr) {
  asm volatile(ELECT_BEGIN "@e mbarrier.arrive.shared::cluster.b64 _, [%0];\n}" ::"r"(cluster_addr) : "memory");
}
__device__ __forceinline__ void arrive_e(uint32_t bar) {
  asm volatile(ELECT_BEGIN "@e mbarrier.arrive.shared::cta.b64 _, [%0];\n}" ::"r"(bar) : "memory");
}
__device__ __forceinline__ void bulk_commit() { asm volatile("cp.async.bulk.commit_group;" ::: "memory"); }
template <int N> __device__ __forceinline__ void bulk_wait() { asm volatile("cp.async.bulk.wait_group %0;" ::"n"(N) : "memory"); }
__device__ __forceinline__ void wg_fence() { asm volatile("wgmma.fence.sync.aligned;" ::: "memory"); }
__device__ __forceinline__ void wg_commit() { asm volatile("wgmma.commit_group.sync.aligned;" ::: "memory"); }
template <int N> __device__ __forceinline__ void wg_wait() { asm volatile("wgmma.wait_group.sync.aligned %0;" ::"n"(N) : "memory"); }
__device__ __forceinline__ void fence_async_global() { asm volatile("fence.proxy.async.global;" ::: "memory"); }
__device__ __forceinline__ void st_relaxed(unsigned int* p, unsigned int v) {
  asm volatile("st.relaxed.gpu.global.u32 [%0], %1;" ::"l"(p), "r"(v) : "memory");
}
__device__ __forceinline__ unsigned int ld_acquire(const unsigned int* p) {
  unsigned int v;
  asm volatile("ld.acquire.gpu.global.u32 %0, [%1];" : "=r"(v) : "l"(p) : "memory");
  return v;
}
__device__ __forceinline__ void ldsm4(uint32_t* r, uint32_t addr) {
  asm volatile("ldmatrix.sync.aligned.m8n8.x4.shared.b16 {%0, %1, %2, %3}, [%4];"
               : "=r"(r[0]), "=r"(r[1]), "=r"(r[2]), "=r"(r[3]) : "r"(addr) : "memory");
}
__device__ __forceinline__ void stsm4(uint32_t addr, const uint32_t* r) {
  asm volatile("stmatrix.sync.aligned.m8n8.x4.shared.b16 [%0], {%1, %2, %3, %4};"
               ::"r"(addr), "r"(r[0]), "r"(r[1]), "r"(r[2]), "r"(r[3]) : "memory");
}
__device__ __forceinline__ void load_partial(float* a, uint32_t addr) {
  asm volatile("ld.shared.v4.f32 {%0, %1, %2, %3}, [%4];"
               : "+f"(a[4]), "+f"(a[5]), "+f"(a[6]), "+f"(a[7]) : "r"(addr) : "memory");
}
__device__ __forceinline__ void widen_partial(float* a) {
  asm volatile("shl.b32 %0, %4, 16;\nand.b32 %1, %4, 0xffff0000;\n"
               "shl.b32 %2, %5, 16;\nand.b32 %3, %5, 0xffff0000;\n"
               "shl.b32 %4, %6, 16;\nand.b32 %5, %6, 0xffff0000;\n"
               "shl.b32 %6, %7, 16;\nand.b32 %7, %7, 0xffff0000;"
               : "+f"(a[0]), "+f"(a[1]), "+f"(a[2]), "+f"(a[3]), "+f"(a[4]), "+f"(a[5]), "+f"(a[6]), "+f"(a[7]));
}
template <bool V> struct Flag { static constexpr bool value = V; };
__device__ __forceinline__ void fence_async_smem() { asm volatile("fence.proxy.async.shared::cta;" ::: "memory"); }
__device__ __forceinline__ void cluster_arrive_relaxed() { asm volatile("barrier.cluster.arrive.relaxed.aligned;" ::: "memory"); }
__device__ __forceinline__ void cluster_wait() { asm volatile("barrier.cluster.wait.acquire.aligned;" ::: "memory"); }
__device__ __forceinline__ void prefetch_map(const CUtensorMap* m) {
  asm volatile("prefetch.tensormap [%0];" ::"l"(m) : "memory");
}
__device__ __forceinline__ void poll_flag(const unsigned int* ptr, unsigned int target) {
  asm volatile(
      "{\n.reg .pred p;\n.reg .u32 c;\n.reg .s32 v;\n"
      "mov.u32 c, 0;\n"
      "LOOP:\n"
      "ld.acquire.gpu.global.s32 v, [%0];\n"
      "sub.s32 v, v, %1;\n"
      "setp.ge.s32 p, v, 0;\n"
      "@p bra DONE;\n"
      "add.u32 c, c, 1;\n"
      "setp.lt.u32 p, c, 4194304;\n"
      "@p bra LOOP;\n"
      "trap;\n"
      "DONE:\n}"
      ::"l"(ptr), "r"(target) : "memory");
}

constexpr uint32_t DESC_HI = (1024u >> 4) | (1u << 30);
__device__ __forceinline__ uint64_t desc(uint32_t lo) { return ((uint64_t)DESC_HI << 32) | lo; }
constexpr uint32_t DESC_A_LBO = 1u << 16;
constexpr uint32_t DESC_B_LBO = (4096u >> 4) << 16;

struct Ring {
  uint32_t slot, phase;
  template <int N> __device__ __forceinline__ void next() {
    if (++slot == N) { slot = 0; phase ^= 1; }
  }
};

__device__ __forceinline__ int kgroup_col(int j, int q) {
  return q == 0 ? j : (q == 1 ? (j ^ 1) : (((j ^ 2) & ~1) + (q - 2)));
}

__device__ __forceinline__ int role_of_cluster(int c) {
  const int a = c - 4;
  const int b = c - 36, r = (b * 37) >> 8;
  const int first = (a & ~7) + (a & 3) * 2 + ((a >> 2) & 1);
  const int second = 32 + r * 8 + ((0x7531640 >> (((b - r * 7) * 4) & 31)) & 7);
  return c >= 2 * kGroups ? c : (c >= 36 ? second : (c >= 4 ? first : 34 + c * 8));
}
__device__ __forceinline__ int helped_round(int grp) { return (grp & 2) ? (grp & 3) - 1 : 3; }
__device__ __forceinline__ int job_of_group(int grp) {
  return (grp & 2) ? (grp & 1) * 8 + (grp >> 2) : 16 + (grp >> 2) * 2 + (grp & 1);
}
__device__ __forceinline__ int job_row(int n) {
  const int grp = n < 16 ? (n & 7) * 4 + 2 + (n >> 3) : ((n - 16) >> 1) * 4 + (n & 1);
  return (helped_round(grp) * kGroups + grp) * 128;
}

#define PROF_START() do {} while (0)
#define PROF_END() do {} while (0)
#define PROF_SVC(idx) do {} while (0)
#define PROF(idx) do {} while (0)
constexpr int PROF_SMEM = 0;

__global__ void __cluster_dims__(2, 1, 1) __launch_bounds__(384, 1)
dcn_kernel(const __grid_constant__ CUtensorMap mx64, const __grid_constant__ CUtensorMap mx32,
           const __grid_constant__ CUtensorMap mo64, const __grid_constant__ CUtensorMap mo32,
           const __grid_constant__ CUtensorMap mw, const __nv_bfloat16* __restrict__ xptr,
           const __nv_bfloat16* __restrict__ wptr, const __nv_bfloat16* __restrict__ bias, __nv_bfloat16* optr) {
  extern __shared__ __align__(1024) uint8_t smem_raw[];
  const uint32_t sb = smem_u32(smem_raw);
  PROF_START();
  const int tid = threadIdx.x;
  const __nv_bfloat16 *px = nullptr, *pw = nullptr;
  if (tid < 32) {
    const uint32_t r = blockIdx.x * 32 + tid;
    px = xptr + (size_t)r * kDim;
    pw = wptr + (size_t)((r & 1023) * 64);
    asm volatile("prefetch.global.L2 [%0];" ::"l"(px));
    asm volatile("prefetch.global.L2 [%0];" ::"l"(pw));
  }
  if (tid == 256) {
    prefetch_map(&mw);
    prefetch_map(&mx64);
    mbar_init(sb + BAR_BFULL, 1);
    mbar_init(sb + BAR_BFULL + 8, 1);
    mbar_init(sb + BAR_AFULL, 1);
    mbar_init(sb + BAR_AFULL + NA * 8, 1);
    asm volatile("fence.mbarrier_init.release.cluster;" ::: "memory");
  }
  const int wid = __shfl_sync(0xffffffffu, tid >> 5, 0);
  const int bid = role_of_cluster(blockIdx.x >> 1) * 2 + (blockIdx.x & 1);
  const int j = bid & 3;
  const int grp = bid >> 2;
  const bool helper = grp == kGroups;
  const int col0 = helper ? kgroup_col(j, 2) * 256 : 0;
  const int row0 = helper ? job_row(0) : grp * 128;
  auto first_loads = [&](int s) {
    const int col = col0 + s * 64;
    expect_load_3d_e(sb + OFF_B + 2 * s * B_SLOT, &mw, sb + BAR_BFULL + 2 * s * 8, 0, col, j * 4);
    expect_load_2d_e<false>(sb + OFF_A + s * A_SLOT, &mx64, sb + BAR_AFULL + s * 8, col, row0);
    expect_load_2d_e<false>(sb + OFF_A + (NA + s) * A_SLOT, &mx64, sb + BAR_AFULL + (NA + s) * 8, col, row0 + 64);
    expect_load_3d_e(sb + OFF_B + (2 * s + 1) * B_SLOT, &mw, sb + BAR_BFULL + (2 * s + 1) * 8, 0, col + 32, j * 4);
  };
  if (wid == 8) first_loads(0);
  __syncthreads();
  const int wg = wid >> 2, warp = wid & 3;
  const uint32_t rank = j & 1;
  const int short_t = (gridDim.x > 4 * kGroups && !helper) ? helped_round(grp) * kLayers : -1;

  if (wg < 2) {
    cluster_arrive_relaxed();
    asm volatile("setmaxnreg.inc.sync.aligned.u32 232;");
    if (tid < 32) asm volatile("prefetch.global.L2 [%0+128];\nprefetch.global.L2 [%1+131072];" ::"l"(px), "l"(pw));
    const int lane = tid & 31;
    const int wtid = tid & 127;
    const uint32_t abase = sb + OFF_A + wg * NA * A_SLOT;
    const uint32_t afull = sb + BAR_AFULL + wg * NA * 8;
    const uint32_t aempty = map_cta(sb + BAR_AEMPTY + wg * NA * 8, wtid == 32 ? (rank ^ 1) : rank);
    const bool rel_a = (wtid == 0) || (wtid == 32);
    const bool rel_b = (wtid == 64);
    const uint32_t frag0 = __shfl_sync(0xffffffffu, abase + ((wtid >> 5) * 16 + ((lane >> 3) & 1) * 8 + (lane & 7)) * 128 +
                                                        (((lane >> 4) ^ (lane & 7)) << 4), lane);
    const uint32_t adesc0 = ((abase & 0x3FFFF) >> 4) | DESC_A_LBO;
    const uint32_t bdesc0 = (((sb + OFF_B) & 0x3FFFF) >> 4) | DESC_B_LBO;

    uint32_t zero;
    asm volatile("mov.u32 %0, %%ctaid.y;" : "=r"(zero));
    float acc[128];
    uint32_t xr[64];
    asm volatile("st.shared.v4.f32 [%0], {%1, %1, %1, %1};" ::"r"(sb + OFF_EXTRA + wid * 16), "f"(kOffset) : "memory");
#pragma unroll
    for (int i = 0; i < 128; i += 4)
      asm volatile("ld.volatile.shared.v4.f32 {%0, %1, %2, %3}, [%4];"
                   : "=f"(acc[i]), "=f"(acc[i + 1]), "=f"(acc[i + 2]), "=f"(acc[i + 3]) : "r"(sb + OFF_EXTRA + wid * 16) : "memory");
#pragma unroll
    for (int i = 0; i < 64; i++) asm volatile("" : "=r"(xr[i]));
    Ring rb{0, 0};
    uint32_t slot_m1 = 0, slot_m2 = 0, slot_m3 = 0;
    uint32_t fpar = 0;
    int l = 0;
    bool hold = false;
    bool swap = false;
    int q_second = helper ? 3 : 1;
    int capture_q = helper ? -1 : j;

    auto release_b = [&](uint32_t slot) {
      if (rel_b) mbar_arrive(sb + BAR_BEMPTY + slot * 8);
    };
    auto release_a = [&](int s) {
      if (rel_a) mbar_arrive_mapped(aempty + s * 8);
    };
    auto chunk_staged = [&](int c) {
      __syncwarp();
      arrive_e(sb + BAR_STAGED + (wg * NA + c) * 8);
    };
    auto capture_slot = [&](int p) {
#pragma unroll
      for (int g = 0; g < 4; g++) ldsm4(&xr[(p * 4 + g) * 4], (frag0 ^ (g * 32)) + p * A_SLOT);
    };
    auto swap_half = [&](int p, int half) {
#pragma unroll
      for (int g = half * 2; g < half * 2 + 2; g++) {
        const uint32_t addr = (frag0 ^ (g * 32)) + p * A_SLOT;
        uint32_t n[4];
        ldsm4(n, addr);
        stsm4(addr, &xr[(p * 4 + g) * 4]);
#pragma unroll
        for (int i = 0; i < 4; i++) xr[(p * 4 + g) * 4 + i] = n[i];
      }
      if (half) chunk_staged(p);
    };
    auto half_step = [&](int q, int s, int h, int t, bool first) {
      if (s == 0 && h == 1 && q == 3 && wg == 1) {
        wg_wait<1>();
        release_b(slot_m2);
        wg_wait<0>();
        release_b(slot_m1);
        if (swap && q_second == 3) { swap_half(3, 0); swap_half(3, 1); }
        release_a(3);
        mbar_spin(sb + BAR_ORDER, t & 1);
      }
      if (!(first && h == 0)) mbar_spin(sb + BAR_BFULL + rb.slot * 8, rb.phase);
      const uint32_t bdesc = bdesc0 + rb.slot * (B_SLOT >> 4);
      const uint32_t adesc = adesc0 + s * (A_SLOT >> 4) + h * 4;
      wg_fence();
      wgmma_ss_n256<0, 1>(acc, desc(adesc), desc(bdesc));
      wgmma_ss_n256<0, 1>(acc, desc(adesc + 2), desc(bdesc + 128));
      wg_commit();
      slot_m3 = slot_m2;
      slot_m2 = slot_m1;
      slot_m1 = rb.slot;
      rb.next<NB>();
      if (s == 3 && h == 1 && q == 3 && wg == 0 && wtid == 96) mbar_arrive(sb + BAR_ORDER);
    };
    auto retire = [&](int q, int s, int h, bool first) {
      if (h == 1 && q == capture_q) capture_slot(s);
      const bool drained = s * 2 + h >= 1 && s * 2 + h <= 2 && q == 3 && wg == 1;
      if (!first && !drained) {
        wg_wait<2>();
        release_b(slot_m3);
        if (h == 1) {
          if (s == 0 || q < 3 || hold) release_a((s + 3) & 3);
          if ((s == 0 || q == 0) && swap && q == (s == 0 ? q_second : 0)) swap_half((s + 3) & 3, 0);
        } else {
          if ((s <= 1) != (q == 0) && swap && q == (s <= 1 ? q_second : 0)) swap_half((s + 2) & 3, 1);
        }
      }
    };

    cluster_wait();
    const int ntiles = helper ? kJobs : kTiles;
    mbar_spin(afull, 0);
    half_step(0, 0, 0, 0, false);
#pragma unroll 1
    for (int t = 0;; t++) {
      hold = (helper || l == kLayers - 1) && (t + 1 < ntiles);
      PROF(t * 32 + wg * 16 + 0);
#pragma unroll
      for (int s = 0; s < 4; s++) {
        if (s > 0) {
          if (l == 0) mbar_spin(afull + s * 8, fpar);
          PROF(t * 32 + wg * 16 + 8 + s);
          half_step(0, s, 0, t, false);
        }
        retire(0, s, 0, s == 0);
        half_step(0, s, 1, t, s == 0);
        retire(0, s, 1, s == 0);
      }
      if (l == 0) fpar ^= 1;
      PROF(t * 32 + wg * 16 + 1);
#pragma unroll 1
      for (int q = q_second; q < 4; q++) {
#pragma unroll
        for (int s = 0; s < 4; s++) {
          mbar_spin(afull + s * 8, fpar);
          if (s == 0) PROF(t * 32 + wg * 16 + 3 + q);
          half_step(q, s, 0, t, false);
          retire(q, s, 0, false);
          half_step(q, s, 1, t, false);
          retire(q, s, 1, false);
        }
        fpar ^= 1;
      }
      if (t == 0 && !helper) mbar_spin(sb + BAR_BIAS, 0);
      const uint32_t bl = sb + OFF_BIAS + l * 512 + (lane & 3) * 16;
      uint32_t bq[8][4];
      auto load_bias = [&](int U) {
        asm volatile("ld.shared.v4.u32 {%0, %1, %2, %3}, [%4];"
                     : "=r"(bq[U][0]), "=r"(bq[U][1]), "=r"(bq[U][2]), "=r"(bq[U][3]) : "r"(bl + U * 64));
      };
#pragma unroll
      for (int U = 0; U < BPRE; U++) load_bias(U);
      uint32_t fa[4];
#pragma unroll
      for (int g = 0; g < 4; g++) asm volatile("xor.b32 %0, %1, %2;" : "=r"(fa[g]) : "r"(frag0), "r"(g * 32));
      wg_wait<1>();
      release_b(slot_m2);
      if (t + 1 < ntiles) mbar_spin(sb + BAR_BFULL + rb.slot * 8, rb.phase);
      wg_wait<0>();
#pragma unroll
      for (int i = 0; i < 128; i++) asm volatile("" : "+f"(acc[i]) :: "memory");
      release_b(slot_m1);
      if (hold) release_a(3);
      PROF(t * 32 + wg * 16 + 2);

      auto pack = [&](int i) {
        uint32_t v;
        asm("cvt.rn.bf16x2.f32 %0, %1, %2;" : "=r"(v) : "f"(acc[i * 2 + 1]), "f"(acc[i * 2]));
        return v;
      };
      auto cross = [&](int T, int i) {
        uint32_t y, o;
        asm("mul.rn.bf16x2 %0, %1, %2;" : "=r"(y) : "r"(xr[T * 4 + i]), "r"(bq[T >> 1][(T & 1) * 2 + (i >> 1)]));
        asm("fma.rn.bf16x2 %0, %1, %2, %3;" : "=r"(o) : "r"(xr[T * 4 + i]), "r"(pack(T * 4 + i)), "r"(y));
        return o;
      };
      auto reset_acc = [&](int T) {
#pragma unroll
        for (int i = T * 8; i < T * 8 + 8; i++)
          asm("{\n.reg .u32 a, c;\nmov.b32 a, %0;\nmov.b32 c, %2;\nmad.lo.u32 a, a, %1, c;\nmov.b32 %0, a;\n}"
              : "+f"(acc[i]) : "r"(zero), "f"(kOffset));
      };
      if (helper) {
        __nv_bfloat16* dst = optr + (size_t)(job_row(t) + (tid >> 5) * 16 + (lane >> 3)) * kDim + j * 256 + (lane & 7) * 8;
        uint64_t pol;
        asm volatile("createpolicy.fractional.L2::evict_first.b64 %0, 1.0;" : "=l"(pol));
#pragma unroll
        for (int T = 0; T < 16; T++) {
          asm volatile("st.global.L2::cache_hint.v4.b32 [%0], {%1, %2, %3, %4}, %5;"
                       ::"l"(dst + (T & 3) * 4 * kDim + (T >> 2) * 64), "r"(pack(T * 4)), "r"(pack(T * 4 + 1)),
                         "r"(pack(T * 4 + 2)), "r"(pack(T * 4 + 3)), "l"(pol) : "memory");
          reset_acc(T);
        }
        asm volatile("bar.sync %0, 128;" ::"r"(wg + 1) : "memory");
        if (wtid == 0) mbar_arrive(sb + BAR_PUB);
      } else if (hold) {
        const bool inject = t + 1 == short_t;
        const uint32_t prow = ((wtid >> 5) * 16 + (lane >> 3)) * 128 + (((lane & 7) ^ (lane >> 3)) << 4);
#pragma unroll
        for (int T = 0; T < 16; T++) {
#pragma unroll
          for (int i = 0; i < 4; i++) xr[T * 4 + i] = cross(T, i);
          if ((T & 1) && (T >> 1) + BPRE < 8) load_bias((T >> 1) + BPRE);
          if ((T & 3) == 3 && !inject) {
#pragma unroll
            for (int g = T - 3; g <= T; g++) reset_acc(g);
          }
          if ((T & 3) == 3 && inject) {
            const int c = T >> 2;
            if (c > 0) mbar_spin(afull + c * 8, fpar);
            else mbar_spin(sb + BAR_EXTRA + wg * 8, 0);
            const uint32_t src = c > 0 ? abase + c * A_SLOT : sb + OFF_EXTRA;
#pragma unroll
            for (int g = 0; g < 4; g++) load_partial(&acc[(c * 4 + g) * 8], src + (prow ^ ((g & 1) * 64)) + g * 512);
            chunk_staged(c);
#pragma unroll
            for (int g = 0; g < 16; g++)
              if ((g >> 2) == c - 1 || (c == 3 && (g >> 2) == 3)) widen_partial(&acc[g * 8]);
            PROF(t * 32 + wg * 16 + 12 + c);
          }
        }
        if (inject) fpar ^= 1;
      } else {
#pragma unroll
        for (int T = 0; T < 16; T++) {
          uint32_t o[4];
#pragma unroll
          for (int i = 0; i < 4; i++) o[i] = cross(T, i);
          stsm4(fa[T & 3] + (T >> 2) * A_SLOT, o);
          if ((T & 3) == 3) chunk_staged(T >> 2);
          if ((T & 1) && (T >> 1) + BPRE < 8) load_bias((T >> 1) + BPRE);
        }
        PROF(t * 32 + wg * 16 + 7);
        fence_async_smem();
        asm volatile("bar.sync %0, 128;" ::"r"(wg + 1) : "memory");
      }
      PROF(t * 32 + wg * 16 + 3);
      if (t + 1 == ntiles) break;
      if (hold) mbar_spin(afull, fpar);
      half_step(0, 0, 0, t, true);
      if (helper || ++l == kLayers) l = 0;
      swap = hold && !helper;
      q_second = (helper || t + 1 == short_t) ? 3 : 1;
      capture_q = -1;
    }
  } else {
    asm volatile("setmaxnreg.dec.sync.aligned.u32 40;");
    if (tid == 256) {
#pragma unroll
      for (int i = 0; i < 22; i++)
        if (i != 0 && i != NA && i != 8 && i != 9) mbar_init(sb + OFF_BAR + i * 8, 1);
      asm volatile("fence.mbarrier_init.release.cluster;" ::: "memory");
    }
    if (tid == 288) {
#pragma unroll
      for (int i = 0; i < NB + 2; i++) mbar_init(sb + BAR_BEMPTY + i * 8, 2);
#pragma unroll
      for (int i = 0; i < 2 * NA; i++) { mbar_init(sb + BAR_AEMPTY + i * 8, 2); mbar_init(sb + BAR_STAGED + i * 8, 4); }
      asm volatile("fence.mbarrier_init.release.cluster;" ::: "memory");
    }
    __syncwarp();
    cluster_arrive_relaxed();
#pragma unroll 1
    for (int s = warp == 0 ? 1 : 4; s < 4; s++) first_loads(s);
    cluster_wait();
    mbar_wait(sb + BAR_AFULL + (warp & 2) * 16, 0);
    if (warp == 0) {
      if (sb & 1023) asm volatile("trap;");
      uint32_t zero;
      asm volatile("mov.u32 %0, %%ctaid.y;" : "=r"(zero));
      const CUtensorMap* mwp = (const CUtensorMap*)((const char*)&mw + zero);
      uint32_t dst = sb + OFF_B + 8 * B_SLOT, bar = sb + BAR_BFULL + 8 * 8, phase = 1;
      int c = 256;
      int mask = helper ? ((j & 2) ^ 2) << 8 : 0;
      int row = c ^ mask;
      const uint32_t relaxed = helper ? 1024 : (NT - 2) * 32;
      int left = helper ? kJobs : kTiles;
#pragma unroll 1
      for (;;) {
        mbar_spin(bar + (BAR_BEMPTY - BAR_BFULL), phase);
        if ((uint32_t)((c - 64) & 1023) >= relaxed) __nanosleep(128);
        load_expect_3d_e(dst, mwp, bar, zero, row, j * 4);
        c += 32;
        dst += B_SLOT;
        bar += 8;
        if (bar == sb + BAR_BFULL + NB * 8) { bar = sb + BAR_BFULL; dst = sb + OFF_B; phase ^= 1; }
        if ((c & 511) == 0) {
          if ((c & 512) && (helper || kTiles - left == short_t)) c += 512;
          if (c & 512) {
            mask &= 512;
          } else {
            if (--left == 0) break;
            if (helper || c == kLayers * kDim) c = 0;
            if (!helper) mask = j << 8;
          }
        }
        row = c ^ mask;
      }
    } else if (warp <= 2) {
      const int w = warp - 1;
      const uint32_t abase = sb + OFF_A + w * NA * A_SLOT;
      const uint32_t fullb = sb + BAR_AFULL + w * NA * 8;
      const uint32_t emptyb = sb + BAR_AEMPTY + w * NA * 8;
      const uint32_t stagedb = sb + BAR_STAGED + w * NA * 8;
      const unsigned int base = __shfl_sync(0xffffffffu, *(volatile unsigned int*)(g_flags + bid * 32), 0);
      uint32_t epar = 0;
      uint32_t spar = 0;
      uint32_t last = 0;
      auto refill = [&](const CUtensorMap* m, int col, int row) {
#pragma unroll 1
        for (int s = 0; s < 4; s++) {
          mbar_wait(emptyb + s * 8, epar);
          expect_load_2d_e<false>(abase + s * A_SLOT, m, fullb + s * 8, col + s * 64, row);
        }
        epar ^= 1;
      };
      auto store_refill = [&](int out_row, int col, int row, bool last_read) {
#pragma unroll 1
        for (int s = 0; s < 4; s++) {
          mbar_wait(stagedb + s * 8, spar);
          fence_async_smem();
          store_2d_e<true>(&mo64, abase + s * A_SLOT, j * 256 + s * 64, out_row);
          bulk_commit();
          bulk_wait<0>();
          __syncwarp();
          mbar_wait(emptyb + s * 8, epar);
          if (last_read) expect_load_2d_e<true>(abase + s * A_SLOT, &mx64, fullb + s * 8, col + s * 64, row);
          else expect_load_2d_e<false>(abase + s * A_SLOT, &mx64, fullb + s * 8, col + s * 64, row);
        }
        spar ^= 1;
        epar ^= 1;
      };
      auto store_tile = [&](auto stream, int out_row) {
#pragma unroll 1
        for (int c = 0; c < 4; c++) {
          mbar_wait(stagedb + c * 8, spar);
          fence_async_smem();
          if (!decltype(stream)::value) pace_wait(last, w ? 640 : 512);
          store_2d_e<decltype(stream)::value>(&mo64, abase + c * A_SLOT, j * 256 + c * 64, out_row);
        }
        spar ^= 1;
        bulk_commit();
        bulk_wait<0>();
        __syncwarp();
      };
      auto refill_shared = [&](const CUtensorMap* m32, int col, int row) {
#pragma unroll 1
        for (int s = 0; s < 4; s++) {
          mbar_wait(emptyb + s * 8, epar);
          expect_load_2d_mc_e(abase + s * A_SLOT + rank * 4096, m32, fullb + s * 8, col + s * 64, row + rank * 32);
        }
        epar ^= 1;
      };
      if (helper) {
#pragma unroll 1
        for (int h = 1; h < 2 * kJobs; h++) refill_shared(&mx32, col0 + (h & 1) * 256, job_row(h >> 1) + w * 64);
      } else {
        const uint32_t xready_peer = map_cta(sb + BAR_XREADY + w * 8, rank ^ 1);
        const unsigned int* oflag = g_flags + (grp * 4 + kgroup_col(j, 2)) * 32;
        unsigned int* done_mine = g_flags + kFlagSet + (bid * 2 + w) * 32;
        const unsigned int* done_peer = g_flags + kFlagSet + ((bid ^ 2) * 2 + w) * 32;
        uint32_t nx = 0;
        uint32_t fpar = 0;
#pragma unroll 1
        for (int rd = 0; rd < kRounds; rd++) {
          const int xrow = (rd * kGroups + grp) * 128 + w * 64;
          if (rd == 0) {
            refill(&mx64, 256, xrow);
          } else {
            poll_flag(done_peer, base + nx);
            store_refill(xrow - kGroups * 128, (j ^ 1) * 256, xrow, rd * kLayers == short_t);
          }
          if (rd * kLayers != short_t) {
#pragma unroll 1
            for (int h = 0; h < 2; h++) refill_shared(&mx32, (kgroup_col(rd == 0 ? 0 : j, 2) + h) * 256, xrow);
          }
          fpar ^= 1;
#pragma unroll 1
          for (int l = 1; l < kLayers; l++) {
            if (l > 1) poll_flag(done_peer, base + nx);
            store_tile(Flag<false>(), xrow);
            PROF_SVC((rd * kLayers + l - 1) * 2 + w);
            arrive_mapped_e(xready_peer);
            arrive_e(sb + BAR_PUB);
            mbar_wait(sb + BAR_XREADY + w * 8, nx & 1);
            fence_async_global();
            refill(&mo64, (j ^ 1) * 256, xrow);
            if (rd * kLayers + l + 1 == short_t) {
              poll_flag(g_flags + (4 * kGroups + j) * 32, base + job_of_group(grp) + 1);
              fence_async_global();
              if (w == 0) expect_load_2d_e<false>(sb + OFF_EXTRA, &mo64, sb + BAR_EXTRA, j * 256, xrow + kGroups * 128);
            }
#pragma unroll 1
            for (int h = 0; h < 2; h++) {
              poll_flag(oflag + h * 32, base + nx + 1);
              fence_async_global();
              refill_shared(&mo32, (kgroup_col(j, 2) + h) * 256, xrow);
            }
            fpar ^= 1;
            if (rank) {
#pragma unroll 1
              for (int s = 0; s < 4; s++) mbar_wait(fullb + s * 8, fpar);
            }
            nx++;
            if ((tid & 31) == 0) st_relaxed(done_mine, base + (nx == kRounds * (kLayers - 1) ? kEpoch : nx));
            __syncwarp();
          }
          const int nrow = xrow + kGroups * 128;
          if (rd + 1 == kRounds) {
            poll_flag(done_peer, base + nx);
            store_tile(Flag<true>(), xrow);
          } else if ((rd + 1) * kLayers == short_t) {
#pragma unroll 1
            for (int s = 0; s < 4; s++) {
              mbar_wait(emptyb + s * 8, epar);
              if (s == 0) {
                arrive_e(fullb);
                mbar_wait(fullb, fpar ^ 1);
              }
              expect_load_2d_e<false>(abase + s * A_SLOT, s > 0 ? &mo64 : &mx64, fullb + s * 8, j * 256 + s * 64, nrow);
            }
            epar ^= 1;
#pragma unroll 1
            for (int s = 0; s < 4; s++) {
              mbar_wait(stagedb + s * 8, spar);
              fence_async_smem();
              if (s > 0) expect_load_2d_e<false>(abase + s * A_SLOT, &mx64, fullb + s * 8, j * 256 + s * 64, nrow);
              else if (w == 0) expect_load_2d_e<false>(sb + OFF_EXTRA, &mo64, sb + BAR_EXTRA + 8, j * 256, nrow + 64);
            }
            spar ^= 1;
          } else {
            refill(&mx64, j * 256, nrow);
            fpar ^= 1;
          }
          PROF_SVC((rd * kLayers + kLayers - 1) * 2 + w);
        }
      }
    } else {
      const int lane = tid & 31;
      unsigned int* myflag = g_flags + bid * 32;
      if (lane == 0) { prefetch_map(&mx32); prefetch_map(&mo64); prefetch_map(&mo32); }
      const unsigned int base = *(volatile unsigned int*)myflag;
      auto publish = [&](uint32_t n, uint32_t value) {
        mbar_wait(sb + BAR_PUB, n & 1);
        asm volatile("fence.acq_rel.gpu;" ::: "memory");
        if (lane == 0) st_relaxed(myflag, base + value);
        __syncwarp();
      };
      if (helper) {
#pragma unroll 1
        for (int n = 0; n < kJobs; n++) {
          if (n + 2 < kJobs) {
            const int row = job_row(n + 2);
#pragma unroll 1
            for (int i = 0; i < 8; i++) prefetch_2d_e(&mx64, col0 + rank * 256 + (i & 3) * 64, row + (i >> 2) * 64);
          }
          publish(n, n + 1);
        }
      } else {
        {
          float c[8];
#pragma unroll
          for (int i = 0; i < 8; i++) c[i] = 1.f - kOffset;
#pragma unroll 1
          for (int l = 0; l < kLayers; l++) {
            const uint4 v = *reinterpret_cast<const uint4*>(bias + l * kDim + j * 256 + lane * 8);
            const uint32_t u[4] = {v.x, v.y, v.z, v.w};
#pragma unroll
            for (int i = 0; i < 4; i++) {
              c[2 * i] += __uint_as_float(u[i] << 16);
              c[2 * i + 1] += __uint_as_float(u[i] & 0xffff0000u);
              uint32_t pk;
              asm("cvt.rn.bf16x2.f32 %0, %1, %2;" : "=r"(pk) : "f"(c[2 * i + 1]), "f"(c[2 * i]));
              asm volatile("st.shared.u32 [%0], %1;" ::"r"(sb + OFF_BIAS + l * 512 + (lane >> 2) * 64 + i * 16 + (lane & 3) * 4),
                           "r"(pk) : "memory");
            }
          }
          __syncwarp();
          if (lane < 2) mbar_arrive(sb + BAR_BIAS);
        }
        const __nv_bfloat16* wslice = wptr + bid * 8192;
        prefetch_1d_e(wslice + kDim * kDim, 16384);
        uint32_t nx = 0;
#pragma unroll 1
        for (int rd = 0; rd < kRounds; rd++) {
#pragma unroll 1
          for (int l = 1; l < kLayers; l++) {
            publish(nx, nx + 1 == kRounds * (kLayers - 1) ? kEpoch : nx + 1);
            nx++;
            if (l < kLayers - 1) {
              if (rd == 0) prefetch_1d_e(wslice + (l + 1) * kDim * kDim, 16384);
            } else if (rd + 1 < kRounds) {
              const int nrow = ((rd + 1) * kGroups + grp) * 128;
              bool partial = false;
              if ((rd + 1) * kLayers == short_t) {
                const unsigned int v = ld_acquire(g_flags + (4 * kGroups + j) * 32);
                partial = __shfl_sync(0xffffffffu, (int)(v - (base + job_of_group(grp) + 1)) >= 0, 0);
              }
#pragma unroll 1
              for (int i = partial ? 0 : 8; i < 16; i++) {
                prefetch_2d_e(i < 8 ? &mo64 : &mx64, j * 256 + ((i >> 1) & 3) * 64, nrow + (i & 1) * 64);
                __nanosleep(i < 8 ? 100 : 300);
              }
            }
          }
        }
      }
    }
    if (warp == (helper ? 3 : 2)) PROF_END();
  }
}

__global__ void __launch_bounds__(256) dcn_fallback(const __nv_bfloat16* __restrict__ x0, const __nv_bfloat16* __restrict__ w,
                                                    const __nv_bfloat16* __restrict__ b, __nv_bfloat16* __restrict__ out) {
  __shared__ float xs[8][kDim];
  const size_t r0 = (size_t)blockIdx.x * 8;
  for (int i = threadIdx.x; i < 8 * kDim; i += 256) xs[i / kDim][i % kDim] = __bfloat162float(x0[r0 * kDim + i]);
  __syncthreads();
  for (int l = 0; l < kLayers; l++) {
    float a[4][8] = {};
    for (int k = 0; k < kDim; k++) {
#pragma unroll
      for (int c = 0; c < 4; c++) {
        const float wv = __bfloat162float(w[((size_t)l * kDim + k) * kDim + c * 256 + threadIdx.x]);
#pragma unroll
        for (int r = 0; r < 8; r++) a[c][r] += xs[r][k] * wv;
      }
    }
    __syncthreads();
#pragma unroll
    for (int c = 0; c < 4; c++) {
      const int n = c * 256 + threadIdx.x;
#pragma unroll
      for (int r = 0; r < 8; r++) {
        const float v = __bfloat162float(x0[(r0 + r) * kDim + n]) * (a[c][r] + __bfloat162float(b[l * kDim + n])) + xs[r][n];
        xs[r][n] = __bfloat162float(__float2bfloat16(v));
      }
    }
    __syncthreads();
  }
  for (int i = threadIdx.x; i < 8 * kDim; i += 256) out[r0 * kDim + i] = __float2bfloat16(xs[i / kDim][i % kDim]);
}

typedef CUresult (*EncodeFn)(CUtensorMap*, CUtensorMapDataType, cuuint32_t, void*, const cuuint64_t*, const cuuint64_t*,
                             const cuuint32_t*, const cuuint32_t*, CUtensorMapInterleave, CUtensorMapSwizzle,
                             CUtensorMapL2promotion, CUtensorMapFloatOOBfill);

static void make_map_2d(EncodeFn enc, CUtensorMap* m, void* ptr, uint64_t rows, uint32_t box_rows) {
  cuuint64_t dims[2] = {(cuuint64_t)kDim, rows};
  cuuint64_t strides[1] = {kDim * 2};
  cuuint32_t box[2] = {64, box_rows};
  cuuint32_t es[2] = {1, 1};
  enc(m, CU_TENSOR_MAP_DATA_TYPE_BFLOAT16, 2, ptr, dims, strides, box, es, CU_TENSOR_MAP_INTERLEAVE_NONE,
      CU_TENSOR_MAP_SWIZZLE_128B, CU_TENSOR_MAP_L2_PROMOTION_L2_128B, CU_TENSOR_MAP_FLOAT_OOB_FILL_NONE);
}

}

extern "C" void kernel_launch(void* const* d_in, const int* in_sizes, int n_in, void* d_out, int out_size) {
  using namespace dcn;
  (void)in_sizes; (void)n_in; (void)out_size;
  void* fn = nullptr;
  cudaDriverEntryPointQueryResult qr;
  cudaGetDriverEntryPoint("cuTensorMapEncodeTiled", &fn, cudaEnableDefault, &qr);
  EncodeFn enc = (EncodeFn)fn;
  CUtensorMap mx64, mx32, mo64, mo32, mw;
  make_map_2d(enc, &mx64, d_in[0], kRows, 64);
  make_map_2d(enc, &mx32, d_in[0], kRows, 32);
  make_map_2d(enc, &mo64, d_out, kRows, 64);
  make_map_2d(enc, &mo32, d_out, kRows, 32);
  {
    cuuint64_t dims[3] = {64, (cuuint64_t)kLayers * kDim, kDim / 64};
    cuuint64_t strides[2] = {kDim * 2, 128};
    cuuint32_t box[3] = {64, 32, 4};
    cuuint32_t es[3] = {1, 1, 1};
    enc(&mw, CU_TENSOR_MAP_DATA_TYPE_BFLOAT16, 3, d_in[1], dims, strides, box, es, CU_TENSOR_MAP_INTERLEAVE_NONE,
        CU_TENSOR_MAP_SWIZZLE_128B, CU_TENSOR_MAP_L2_PROMOTION_L2_128B, CU_TENSOR_MAP_FLOAT_OOB_FILL_NONE);
  }
  const __nv_bfloat16* x0 = (const __nv_bfloat16*)d_in[0];
  const __nv_bfloat16* w = (const __nv_bfloat16*)d_in[1];
  const __nv_bfloat16* b = (const __nv_bfloat16*)d_in[2];
  __nv_bfloat16* out = (__nv_bfloat16*)d_out;
  constexpr int smem = SMEM_BYTES + PROF_SMEM;
  cudaFuncSetAttribute(dcn_kernel, cudaFuncAttributeMaxDynamicSharedMemorySize, smem);

  cudaLaunchConfig_t cfg = {};
  cfg.gridDim = dim3(4 * kGroups + 4);
  cfg.blockDim = dim3(384);
  cfg.dynamicSmemBytes = smem;
  cudaLaunchAttribute attr;
  attr.id = cudaLaunchAttributeClusterDimension;
  attr.val.clusterDim.x = 2;
  attr.val.clusterDim.y = 1;
  attr.val.clusterDim.z = 1;
  cfg.attrs = &attr;
  cfg.numAttrs = 1;
  int clusters = 0;
  cudaOccupancyMaxActiveClusters(&clusters, dcn_kernel, &cfg);
  if (clusters >= 2 * kGroups) {
    const int grid = 4 * kGroups + (clusters >= 2 * kGroups + 2 ? 4 : 0);
    dcn_kernel<<<grid, 384, smem>>>(mx64, mx32, mo64, mo32, mw, x0, w, b, out);
  } else {
    dcn_fallback<<<kRows / 8, 256>>>(x0, w, b, out);
  }
}
```

```cpp
#include <cuda_runtime.h>
#include <cuda.h>
#include <cuda_bf16.h>
#include <stdint.h>

namespace dcn {

template <int TA, int TB> __device__ __forceinline__ void wgmma_ss_n256(float (&d)[128], uint64_t da, uint64_t db) {
  asm volatile("{\n.reg .pred p;\nsetp.ne.b32 p, %130, 0;\n"
    "wgmma.mma_async.sync.aligned.m64n256k16.f32.bf16.bf16 "
    "{%0, %1, %2, %3, %4, %5, %6, %7, %8, %9, %10, %11, %12, %13, %14, %15, %16, %17, %18, %19, %20, %21, %22, %23, %24, %25, %26, %27, %28, %29, %30, %31, %32, %33, %34, %35, %36, %37, %38, %39, %40, %41, %42, %43, %44, %45, %46, %47, %48, %49, %50, %51, %52, %53, %54, %55, %56, %57, %58, %59, %60, %61, %62, %63, %64, %65, %66, %67, %68, %69, %70, %71, %72, %73, %74, %75, %76, %77, %78, %79, %80, %81, %82, %83, %84, %85, %86, %87, %88, %89, %90, %91, %92, %93, %94, %95, %96, %97, %98, %99, %100, %101, %102, %103, %104, %105, %106, %107, %108, %109, %110, %111, %112, %113, %114, %115, %116, %117, %118, %119, %120, %121, %122, %123, %124, %125, %126, %127}, "
    "%128, %129, p, 1, 1, %131, %132;\n}\n"
    : "+f"(d[0]), "+f"(d[1]), "+f"(d[2]), "+f"(d[3]), "+f"(d[4]), "+f"(d[5]), "+f"(d[6]), "+f"(d[7]), "+f"(d[8]), "+f"(d[9]), "+f"(d[10]), "+f"(d[11]), "+f"(d[12]), "+f"(d[13]), "+f"(d[14]), "+f"(d[15]), "+f"(d[16]), "+f"(d[17]), "+f"(d[18]), "+f"(d[19]), "+f"(d[20]), "+f"(d[21]), "+f"(d[22]), "+f"(d[23]), "+f"(d[24]), "+f"(d[25]), "+f"(d[26]), "+f"(d[27]), "+f"(d[28]), "+f"(d[29]), "+f"(d[30]), "+f"(d[31]), "+f"(d[32]), "+f"(d[33]), "+f"(d[34]), "+f"(d[35]), "+f"(d[36]), "+f"(d[37]), "+f"(d[38]), "+f"(d[39]), "+f"(d[40]), "+f"(d[41]), "+f"(d[42]), "+f"(d[43]), "+f"(d[44]), "+f"(d[45]), "+f"(d[46]), "+f"(d[47]), "+f"(d[48]), "+f"(d[49]), "+f"(d[50]), "+f"(d[51]), "+f"(d[52]), "+f"(d[53]), "+f"(d[54]), "+f"(d[55]), "+f"(d[56]), "+f"(d[57]), "+f"(d[58]), "+f"(d[59]), "+f"(d[60]), "+f"(d[61]), "+f"(d[62]), "+f"(d[63]), "+f"(d[64]), "+f"(d[65]), "+f"(d[66]), "+f"(d[67]), "+f"(d[68]), "+f"(d[69]), "+f"(d[70]), "+f"(d[71]), "+f"(d[72]), "+f"(d[73]), "+f"(d[74]), "+f"(d[75]), "+f"(d[76]), "+f"(d[77]), "+f"(d[78]), "+f"(d[79]), "+f"(d[80]), "+f"(d[81]), "+f"(d[82]), "+f"(d[83]), "+f"(d[84]), "+f"(d[85]), "+f"(d[86]), "+f"(d[87]), "+f"(d[88]), "+f"(d[89]), "+f"(d[90]), "+f"(d[91]), "+f"(d[92]), "+f"(d[93]), "+f"(d[94]), "+f"(d[95]), "+f"(d[96]), "+f"(d[97]), "+f"(d[98]), "+f"(d[99]), "+f"(d[100]), "+f"(d[101]), "+f"(d[102]), "+f"(d[103]), "+f"(d[104]), "+f"(d[105]), "+f"(d[106]), "+f"(d[107]), "+f"(d[108]), "+f"(d[109]), "+f"(d[110]), "+f"(d[111]), "+f"(d[112]), "+f"(d[113]), "+f"(d[114]), "+f"(d[115]), "+f"(d[116]), "+f"(d[117]), "+f"(d[118]), "+f"(d[119]), "+f"(d[120]), "+f"(d[121]), "+f"(d[122]), "+f"(d[123]), "+f"(d[124]), "+f"(d[125]), "+f"(d[126]), "+f"(d[127])
    : "l"(da), "l"(db), "n"(1), "n"(TA), "n"(TB));
}

constexpr int kDim = 1024;
constexpr int kRows = 16384;
constexpr int kLayers = 6;
constexpr int kGroups = 32;
constexpr int kRounds = kRows / 128 / kGroups;
constexpr int kTiles = kRounds * kLayers;

constexpr float kOffset = 171.f / 128.f;
constexpr int kJobs = kGroups;
constexpr int kEpoch = 32;
constexpr int NA = 4;
constexpr int NB = 9;
constexpr int BPRE = 4;
constexpr int NT = 11;
constexpr int A_SLOT = 8192;
constexpr int B_SLOT = 16384;
constexpr int OFF_B = 0;
constexpr int OFF_A = OFF_B + NB * B_SLOT;
constexpr int OFF_EXTRA = OFF_A + 2 * NA * A_SLOT;
constexpr int OFF_BIAS = OFF_EXTRA + A_SLOT;
constexpr int OFF_BAR = OFF_BIAS + kLayers * 256 * 2;
constexpr int BAR_AFULL = OFF_BAR;
constexpr int BAR_BFULL = OFF_BAR + 64;
constexpr int BAR_ORDER = BAR_BFULL + NB * 8;
constexpr int BAR_XREADY = BAR_ORDER + 8;
constexpr int BAR_EXTRA = BAR_XREADY + 16;
constexpr int BAR_BEMPTY = OFF_BAR + 3 * 64;
constexpr int BAR_BIAS = BAR_BEMPTY + NB * 8;
constexpr int BAR_PUB = BAR_BIAS + 8;
constexpr int OFF_PEER = BAR_PUB + 8;
constexpr int BAR_AEMPTY = OFF_BAR + 5 * 64;
constexpr int BAR_STAGED = OFF_BAR + 6 * 64;
constexpr int SMEM_BYTES = OFF_BAR + 7 * 64;
static_assert(BAR_EXTRA + 16 == OFF_BAR + 22 * 8 && NA == 4, "barrier groups");
static_assert(SMEM_BYTES <= 232448, "shared memory budget");

constexpr int kFlagSet = 4 * (kGroups + 1) * 32;
__device__ unsigned int g_flags[3 * kFlagSet];

__device__ __forceinline__ uint32_t smem_u32(const void* p) { return (uint32_t)__cvta_generic_to_shared(p); }
__device__ __forceinline__ void mbar_init(uint32_t bar, int cnt) {
  asm volatile("mbarrier.init.shared::cta.b64 [%0], %1;" ::"r"(bar), "r"(cnt) : "memory");
}
__device__ __forceinline__ void mbar_arrive(uint32_t bar) {
  asm volatile("mbarrier.arrive.shared::cta.b64 _, [%0];" ::"r"(bar) : "memory");
}
__device__ __forceinline__ uint32_t map_cta(uint32_t addr, uint32_t cta) {
  uint32_t r;
  asm volatile("mapa.shared::cluster.u32 %0, %1, %2;" : "=r"(r) : "r"(addr), "r"(cta));
  return r;
}
__device__ __forceinline__ void mbar_arrive_mapped(uint32_t cluster_addr) {
  asm volatile("mbarrier.arrive.shared::cluster.b64 _, [%0];" ::"r"(cluster_addr) : "memory");
}
__device__ __forceinline__ void mbar_wait(uint32_t bar, uint32_t parity) {
  asm volatile(
      "{\n.reg .pred p;\n.reg .u32 c;\n"
      "mbarrier.try_wait.parity.shared::cta.b64 p, [%0], %1;\n"
      "@p bra DONE;\n"
      "mov.u32 c, 0;\n"
      "LOOP:\n"
      "mbarrier.try_wait.parity.shared::cta.b64 p, [%0], %1;\n"
      "@p bra DONE;\n"
      "add.u32 c, c, 1;\n"
      "setp.lt.u32 p, c, 4194304;\n"
      "@p bra LOOP;\n"
      "trap;\n"
      "DONE:\n}"
      ::"r"(bar), "r"(parity) : "memory");
}
__device__ __forceinline__ void mbar_spin(uint32_t bar, uint32_t parity) {
  asm volatile(
      "{\n.reg .pred p;\n"
      "LOOP:\n"
      "mbarrier.try_wait.parity.shared::cta.b64 p, [%0], %1;\n"
      "@!p bra LOOP;\n}"
      ::"r"(bar), "r"(parity) : "memory");
}
#define ELECT_BEGIN "{\n.reg .pred e;\nelect.sync _|e, 0xffffffff;\n"
template <bool STREAM> __device__ __forceinline__ void expect_load_2d_e(uint32_t dst, const CUtensorMap* m, uint32_t bar, int c0, int c1) {
  if (STREAM) {
    asm volatile(ELECT_BEGIN ".reg .b64 pol;\ncreatepolicy.fractional.L2::evict_first.b64 pol, 1.0;\n"
                 "@e mbarrier.arrive.expect_tx.shared::cta.b64 _, [%2], 8192;\n"
                 "@e cp.async.bulk.tensor.2d.shared::cluster.global.mbarrier::complete_tx::bytes.L2::cache_hint [%0], [%1, {%3, %4}], [%2], pol;\n}"
                 ::"r"(dst), "l"(m), "r"(bar), "r"(c0), "r"(c1) : "memory");
  } else {
    asm volatile(ELECT_BEGIN
                 "@e mbarrier.arrive.expect_tx.shared::cta.b64 _, [%2], 8192;\n"
                 "@e cp.async.bulk.tensor.2d.shared::cluster.global.mbarrier::complete_tx::bytes [%0], [%1, {%3, %4}], [%2];\n}"
                 ::"r"(dst), "l"(m), "r"(bar), "r"(c0), "r"(c1) : "memory");
  }
}
__device__ __forceinline__ void expect_load_2d_mc_e(uint32_t dst, const CUtensorMap* m, uint32_t bar, int c0, int c1) {
  asm volatile(ELECT_BEGIN ".reg .b64 pol;\ncreatepolicy.fractional.L2::evict_first.b64 pol, 1.0;\n"
               "@e mbarrier.arrive.expect_tx.shared::cta.b64 _, [%2], 8192;\n"
               "@e cp.async.bulk.tensor.2d.shared::cluster.global.mbarrier::complete_tx::bytes.multicast::cluster.L2::cache_hint [%0], [%1, {%3, %4}], [%2], %5, pol;\n}"
               ::"r"(dst), "l"(m), "r"(bar), "r"(c0), "r"(c1), "h"((uint16_t)3) : "memory");
}
__device__ __forceinline__ void expect_load_3d_e(uint32_t dst, const CUtensorMap* m, uint32_t bar, int c0, int c1, int c2) {
  asm volatile(ELECT_BEGIN
               "@e mbarrier.arrive.expect_tx.shared::cta.b64 _, [%2], 16384;\n"
               "@e cp.async.bulk.tensor.3d.shared::cluster.global.mbarrier::complete_tx::bytes [%0], [%1, {%3, %4, %5}], [%2];\n}"
               ::"r"(dst), "l"(m), "r"(bar), "r"(c0), "r"(c1), "r"(c2) : "memory");
}
template <bool STREAM> __device__ __forceinline__ void store_2d_e(const CUtensorMap* m, uint32_t src, int c0, int c1) {
  if (STREAM) {
    asm volatile(ELECT_BEGIN ".reg .b64 pol;\ncreatepolicy.fractional.L2::evict_first.b64 pol, 1.0;\n"
                 "@e cp.async.bulk.tensor.2d.global.shared::cta.bulk_group.L2::cache_hint [%0, {%2, %3}], [%1], pol;\n}"
                 ::"l"(m), "r"(src), "r"(c0), "r"(c1) : "memory");
  } else {
    asm volatile(ELECT_BEGIN
                 "@e cp.async.bulk.tensor.2d.global.shared::cta.bulk_group [%0, {%2, %3}], [%1];\n}"
                 ::"l"(m), "r"(src), "r"(c0), "r"(c1) : "memory");
  }
}
__device__ __forceinline__ void prefetch_2d_e(const CUtensorMap* m, int c0, int c1) {
  asm volatile(ELECT_BEGIN
               "@e cp.async.bulk.prefetch.tensor.2d.L2.global [%0, {%1, %2}];\n}"
               ::"l"(m), "r"(c0), "r"(c1) : "memory");
}
__device__ __forceinline__ void prefetch_1d_e(const void* ptr, uint32_t bytes) {
  asm volatile(ELECT_BEGIN
               "@e cp.async.bulk.prefetch.L2.global [%0], %1;\n}"
               ::"l"(ptr), "r"(bytes) : "memory");
}
__device__ __forceinline__ void load_expect_3d_e(uint32_t dst, const CUtensorMap* m, uint32_t bar, int c0, int c1, int c2) {
  asm volatile(ELECT_BEGIN
               "@e cp.async.bulk.tensor.3d.shared::cluster.global.mbarrier::complete_tx::bytes [%0], [%1, {%3, %4, %5}], [%2];\n"
               "@e mbarrier.arrive.expect_tx.shared::cta.b64 _, [%2], 16384;\n}"
               ::"r"(dst), "l"(m), "r"(bar), "r"(c0), "r"(c1), "r"(c2) : "memory");
}
__device__ __forceinline__ void pace_wait(uint32_t& last, uint32_t gap) {
  asm volatile("{\n.reg .pred p;\n.reg .u32 b, d;\n"
               "AGAIN:\n"
               "mov.u32 b, %%clock;\n"
               "sub.u32 d, b, %0;\n"
               "setp.lt.u32 p, d, %1;\n"
               "@p bra.uni AGAIN;\n"
               "mov.u32 %0, b;\n}" : "+r"(last) : "r"(gap) : "memory");
}
__device__ __forceinline__ void arrive_mapped_e(uint32_t cluster_addr) {
  asm volatile(ELECT_BEGIN "@e mbarrier.arrive.shared::cluster.b64 _, [%0];\n}" ::"r"(cluster_addr) : "memory");
}
__device__ __forceinline__ void arrive_e(uint32_t bar) {
  asm volatile(ELECT_BEGIN "@e mbarrier.arrive.shared::cta.b64 _, [%0];\n}" ::"r"(bar) : "memory");
}
__device__ __forceinline__ void bulk_commit() { asm volatile("cp.async.bulk.commit_group;" ::: "memory"); }
template <int N> __device__ __forceinline__ void bulk_wait() { asm volatile("cp.async.bulk.wait_group %0;" ::"n"(N) : "memory"); }
__device__ __forceinline__ void wg_fence() { asm volatile("wgmma.fence.sync.aligned;" ::: "memory"); }
__device__ __forceinline__ void wg_commit() { asm volatile("wgmma.commit_group.sync.aligned;" ::: "memory"); }
template <int N> __device__ __forceinline__ void wg_wait() { asm volatile("wgmma.wait_group.sync.aligned %0;" ::"n"(N) : "memory"); }
__device__ __forceinline__ void fence_async_global() { asm volatile("fence.proxy.async.global;" ::: "memory"); }
__device__ __forceinline__ void st_relaxed(unsigned int* p, unsigned int v) {
  asm volatile("st.relaxed.gpu.global.u32 [%0], %1;" ::"l"(p), "r"(v) : "memory");
}
__device__ __forceinline__ unsigned int ld_acquire(const unsigned int* p) {
  unsigned int v;
  asm volatile("ld.acquire.gpu.global.u32 %0, [%1];" : "=r"(v) : "l"(p) : "memory");
  return v;
}
__device__ __forceinline__ void ldsm4(uint32_t* r, uint32_t addr) {
  asm volatile("ldmatrix.sync.aligned.m8n8.x4.shared.b16 {%0, %1, %2, %3}, [%4];"
               : "=r"(r[0]), "=r"(r[1]), "=r"(r[2]), "=r"(r[3]) : "r"(addr) : "memory");
}
__device__ __forceinline__ void stsm4(uint32_t addr, const uint32_t* r) {
  asm volatile("stmatrix.sync.aligned.m8n8.x4.shared.b16 [%0], {%1, %2, %3, %4};"
               ::"r"(addr), "r"(r[0]), "r"(r[1]), "r"(r[2]), "r"(r[3]) : "memory");
}
__device__ __forceinline__ void load_partial(float* a, uint32_t addr) {
  asm volatile("ld.shared.v4.f32 {%0, %1, %2, %3}, [%4];"
               : "+f"(a[4]), "+f"(a[5]), "+f"(a[6]), "+f"(a[7]) : "r"(addr) : "memory");
}
__device__ __forceinline__ void widen_partial(float* a) {
  asm volatile("shl.b32 %0, %4, 16;\nand.b32 %1, %4, 0xffff0000;\n"
               "shl.b32 %2, %5, 16;\nand.b32 %3, %5, 0xffff0000;\n"
               "shl.b32 %4, %6, 16;\nand.b32 %5, %6, 0xffff0000;\n"
               "shl.b32 %6, %7, 16;\nand.b32 %7, %7, 0xffff0000;"
               : "+f"(a[0]), "+f"(a[1]), "+f"(a[2]), "+f"(a[3]), "+f"(a[4]), "+f"(a[5]), "+f"(a[6]), "+f"(a[7]));
}
template <bool V> struct Flag { static constexpr bool value = V; };
__device__ __forceinline__ void fence_async_smem() { asm volatile("fence.proxy.async.shared::cta;" ::: "memory"); }
__device__ __forceinline__ void cluster_arrive_relaxed() { asm volatile("barrier.cluster.arrive.relaxed.aligned;" ::: "memory"); }
__device__ __forceinline__ void cluster_wait() { asm volatile("barrier.cluster.wait.acquire.aligned;" ::: "memory"); }
__device__ __forceinline__ void prefetch_map(const CUtensorMap* m) {
  asm volatile("prefetch.tensormap [%0];" ::"l"(m) : "memory");
}
__device__ __forceinline__ void poll_flag(const unsigned int* ptr, unsigned int target) {
  asm volatile(
      "{\n.reg .pred p;\n.reg .u32 c;\n.reg .s32 v;\n"
      "mov.u32 c, 0;\n"
      "LOOP:\n"
      "ld.acquire.gpu.global.s32 v, [%0];\n"
      "sub.s32 v, v, %1;\n"
      "setp.ge.s32 p, v, 0;\n"
      "@p bra DONE;\n"
      "add.u32 c, c, 1;\n"
      "setp.lt.u32 p, c, 4194304;\n"
      "@p bra LOOP;\n"
      "trap;\n"
      "DONE:\n}"
      ::"l"(ptr), "r"(target) : "memory");
}

constexpr uint32_t DESC_HI = (1024u >> 4) | (1u << 30);
__device__ __forceinline__ uint64_t desc(uint32_t lo) { return ((uint64_t)DESC_HI << 32) | lo; }
constexpr uint32_t DESC_A_LBO = 1u << 16;
constexpr uint32_t DESC_B_LBO = (4096u >> 4) << 16;

struct Ring {
  uint32_t slot, phase;
  template <int N> __device__ __forceinline__ void next() {
    if (++slot == N) { slot = 0; phase ^= 1; }
  }
};

__device__ __forceinline__ int kgroup_col(int j, int q) {
  return q == 0 ? j : (q == 1 ? (j ^ 1) : (((j ^ 2) & ~1) + (q - 2)));
}

__device__ __forceinline__ int role_of_pair(int t) {
  const int b = t - 32, r = (b * 37) >> 8;
  const int gpc = t < 32 ? t : (t < 60 ? 1 + b - r * 7 : 0);
  const int pass = t < 32 ? t >> 3 : (t < 60 ? 4 + r : t - 58);
  return (t >> 1) == 30 ? t + 4 : pass * 8 + ((0x51703246 >> ((gpc * 4) & 31)) & 7);
}
__device__ __forceinline__ int helped_round(int grp) { return (grp & 2) ? (grp & 3) - 1 : 3; }
__device__ __forceinline__ int job_of_group(int grp) {
  return (grp & 2) ? (grp & 1) * 8 + (grp >> 2) : 16 + (grp >> 2) * 2 + (grp & 1);
}
__device__ __forceinline__ int job_row(int n) {
  const int grp = n < 16 ? (n & 7) * 4 + 2 + (n >> 3) : ((n - 16) >> 1) * 4 + (n & 1);
  return (helped_round(grp) * kGroups + grp) * 128;
}

#define PROF_START() do {} while (0)
#define PROF_END() do {} while (0)
#define PROF_SVC(idx) do {} while (0)
#define PROF(idx) do {} while (0)
constexpr int PROF_SMEM = 0;

template <bool BY_SM>
__global__ void __cluster_dims__(2, 1, 1) __launch_bounds__(384, 1)
dcn_kernel(const __grid_constant__ CUtensorMap mx64, const __grid_constant__ CUtensorMap mx32,
           const __grid_constant__ CUtensorMap mo64, const __grid_constant__ CUtensorMap mo32,
           const __grid_constant__ CUtensorMap mw, const __nv_bfloat16* __restrict__ xptr,
           const __nv_bfloat16* __restrict__ wptr, const __nv_bfloat16* __restrict__ bias, __nv_bfloat16* optr) {
  extern __shared__ __align__(1024) uint8_t smem_raw[];
  const uint32_t sb = smem_u32(smem_raw);
  PROF_START();
  const int tid = threadIdx.x;
  const __nv_bfloat16 *px = nullptr, *pw = nullptr;
  if (tid < 32) {
    const uint32_t r = blockIdx.x * 32 + tid;
    px = xptr + (size_t)r * kDim;
    pw = wptr + (size_t)((r & 1023) * 64);
    asm volatile("prefetch.global.L2 [%0];" ::"l"(px));
    asm volatile("prefetch.global.L2 [%0];" ::"l"(pw));
  }
  if (tid == 256) {
    prefetch_map(&mw);
    prefetch_map(&mx64);
    mbar_init(sb + BAR_BFULL, 1);
    mbar_init(sb + BAR_BFULL + 8, 1);
    mbar_init(sb + BAR_AFULL, 1);
    mbar_init(sb + BAR_AFULL + NA * 8, 1);
    asm volatile("fence.mbarrier_init.release.cluster;" ::: "memory");
  }
  const int wid = __shfl_sync(0xffffffffu, tid >> 5, 0);
  uint32_t place = blockIdx.x + (blockIdx.x < 8 ? 124 : -8);
  if (BY_SM) asm volatile("mov.u32 %0, %%smid;" : "=r"(place));
  const int bid = role_of_pair(place >> 1) * 2 + (place & 1);
  const int j = bid & 3;
  const int grp = bid >> 2;
  const bool helper = grp == kGroups;
  const int col0 = helper ? kgroup_col(j, 2) * 256 : 0;
  const int row0 = helper ? job_row(0) : grp * 128;
  auto first_loads = [&](int s) {
    const int col = col0 + s * 64;
    expect_load_3d_e(sb + OFF_B + 2 * s * B_SLOT, &mw, sb + BAR_BFULL + 2 * s * 8, 0, col, j * 4);
    expect_load_2d_e<false>(sb + OFF_A + s * A_SLOT, &mx64, sb + BAR_AFULL + s * 8, col, row0);
    expect_load_2d_e<false>(sb + OFF_A + (NA + s) * A_SLOT, &mx64, sb + BAR_AFULL + (NA + s) * 8, col, row0 + 64);
    expect_load_3d_e(sb + OFF_B + (2 * s + 1) * B_SLOT, &mw, sb + BAR_BFULL + (2 * s + 1) * 8, 0, col + 32, j * 4);
  };
  if (wid == 8) first_loads(0);
  __syncthreads();
  const int wg = wid >> 2, warp = wid & 3;
  const uint32_t rank = j & 1;
  const int short_t = ((BY_SM || gridDim.x > 4 * kGroups) && !helper) ? helped_round(grp) * kLayers : -1;

  if (wg < 2) {
    cluster_arrive_relaxed();
    asm volatile("setmaxnreg.inc.sync.aligned.u32 232;");
    if (tid < 32) asm volatile("prefetch.global.L2 [%0+128];\nprefetch.global.L2 [%1+131072];" ::"l"(px), "l"(pw));
    const int lane = tid & 31;
    const int wtid = tid & 127;
    const uint32_t abase = sb + OFF_A + wg * NA * A_SLOT;
    const uint32_t afull = sb + BAR_AFULL + wg * NA * 8;
    const uint32_t aempty = map_cta(sb + BAR_AEMPTY + wg * NA * 8, wtid == 32 ? (rank ^ 1) : rank);
    const bool rel_a = (wtid == 0) || (wtid == 32);
    const bool rel_b = (wtid == 64);
    const uint32_t frag0 = __shfl_sync(0xffffffffu, abase + ((wtid >> 5) * 16 + ((lane >> 3) & 1) * 8 + (lane & 7)) * 128 +
                                                        (((lane >> 4) ^ (lane & 7)) << 4), lane);
    const uint32_t adesc0 = ((abase & 0x3FFFF) >> 4) | DESC_A_LBO;
    const uint32_t bdesc0 = (((sb + OFF_B) & 0x3FFFF) >> 4) | DESC_B_LBO;

    uint32_t zero;
    asm volatile("mov.u32 %0, %%ctaid.y;" : "=r"(zero));
    float acc[128];
    uint32_t xr[64];
    asm volatile("st.shared.v4.f32 [%0], {%1, %1, %1, %1};" ::"r"(sb + OFF_EXTRA + wid * 16), "f"(kOffset) : "memory");
#pragma unroll
    for (int i = 0; i < 128; i += 4)
      asm volatile("ld.volatile.shared.v4.f32 {%0, %1, %2, %3}, [%4];"
                   : "=f"(acc[i]), "=f"(acc[i + 1]), "=f"(acc[i + 2]), "=f"(acc[i + 3]) : "r"(sb + OFF_EXTRA + wid * 16) : "memory");
#pragma unroll
    for (int i = 0; i < 64; i++) asm volatile("" : "=r"(xr[i]));
    Ring rb{0, 0};
    uint32_t slot_m1 = 0, slot_m2 = 0, slot_m3 = 0;
    uint32_t fpar = 0;
    int l = 0;
    bool hold = false;
    bool swap = false;
    int q_second = helper ? 3 : 1;
    int capture_q = helper ? -1 : j;

    auto release_b = [&](uint32_t slot) {
      if (rel_b) mbar_arrive(sb + BAR_BEMPTY + slot * 8);
    };
    auto release_a = [&](int s) {
      if (rel_a) mbar_arrive_mapped(aempty + s * 8);
    };
    auto chunk_staged = [&](int c) {
      __syncwarp();
      arrive_e(sb + BAR_STAGED + (wg * NA + c) * 8);
    };
    auto capture_slot = [&](int p) {
#pragma unroll
      for (int g = 0; g < 4; g++) ldsm4(&xr[(p * 4 + g) * 4], (frag0 ^ (g * 32)) + p * A_SLOT);
    };
    auto swap_half = [&](int p, int half) {
#pragma unroll
      for (int g = half * 2; g < half * 2 + 2; g++) {
        const uint32_t addr = (frag0 ^ (g * 32)) + p * A_SLOT;
        uint32_t n[4];
        ldsm4(n, addr);
        stsm4(addr, &xr[(p * 4 + g) * 4]);
#pragma unroll
        for (int i = 0; i < 4; i++) xr[(p * 4 + g) * 4 + i] = n[i];
      }
      if (half) chunk_staged(p);
    };
    auto half_step = [&](int q, int s, int h, int t, bool first) {
      if (s == 0 && h == 1 && q == 3 && wg == 1) {
        wg_wait<1>();
        release_b(slot_m2);
        wg_wait<0>();
        release_b(slot_m1);
        if (swap && q_second == 3) { swap_half(3, 0); swap_half(3, 1); }
        release_a(3);
        mbar_spin(sb + BAR_ORDER, t & 1);
      }
      if (!(first && h == 0)) mbar_spin(sb + BAR_BFULL + rb.slot * 8, rb.phase);
      const uint32_t bdesc = bdesc0 + rb.slot * (B_SLOT >> 4);
      const uint32_t adesc = adesc0 + s * (A_SLOT >> 4) + h * 4;
      wg_fence();
      wgmma_ss_n256<0, 1>(acc, desc(adesc), desc(bdesc));
      wgmma_ss_n256<0, 1>(acc, desc(adesc + 2), desc(bdesc + 128));
      wg_commit();
      slot_m3 = slot_m2;
      slot_m2 = slot_m1;
      slot_m1 = rb.slot;
      rb.next<NB>();
      if (s == 3 && h == 1 && q == 3 && wg == 0 && wtid == 96) mbar_arrive(sb + BAR_ORDER);
    };
    auto retire = [&](int q, int s, int h, bool first) {
      if (h == 1 && q == capture_q) capture_slot(s);
      const bool drained = s * 2 + h >= 1 && s * 2 + h <= 2 && q == 3 && wg == 1;
      if (!first && !drained) {
        wg_wait<2>();
        release_b(slot_m3);
        if (h == 1) {
          if (s == 0 || q < 3 || hold) release_a((s + 3) & 3);
          if ((s == 0 || q == 0) && swap && q == (s == 0 ? q_second : 0)) swap_half((s + 3) & 3, 0);
        } else {
          if ((s <= 1) != (q == 0) && swap && q == (s <= 1 ? q_second : 0)) swap_half((s + 2) & 3, 1);
        }
      }
    };

    cluster_wait();
    const int ntiles = helper ? kJobs : kTiles;
    mbar_spin(afull, 0);
    half_step(0, 0, 0, 0, false);
#pragma unroll 1
    for (int t = 0;; t++) {
      hold = (helper || l == kLayers - 1) && (t + 1 < ntiles);
      PROF(t * 32 + wg * 16 + 0);
#pragma unroll
      for (int s = 0; s < 4; s++) {
        if (s > 0) {
          if (l == 0) mbar_spin(afull + s * 8, fpar);
          PROF(t * 32 + wg * 16 + 8 + s);
          half_step(0, s, 0, t, false);
        }
        retire(0, s, 0, s == 0);
        half_step(0, s, 1, t, s == 0);
        retire(0, s, 1, s == 0);
      }
      if (l == 0) fpar ^= 1;
      PROF(t * 32 + wg * 16 + 1);
#pragma unroll 1
      for (int q = q_second; q < 4; q++) {
#pragma unroll
        for (int s = 0; s < 4; s++) {
          mbar_spin(afull + s * 8, fpar);
          if (s == 0) PROF(t * 32 + wg * 16 + 3 + q);
          half_step(q, s, 0, t, false);
          retire(q, s, 0, false);
          half_step(q, s, 1, t, false);
          retire(q, s, 1, false);
        }
        fpar ^= 1;
      }
      if (t == 0 && !helper) mbar_spin(sb + BAR_BIAS, 0);
      const uint32_t bl = sb + OFF_BIAS + l * 512 + (lane & 3) * 16;
      uint32_t bq[8][4];
      auto load_bias = [&](int U) {
        asm volatile("ld.shared.v4.u32 {%0, %1, %2, %3}, [%4];"
                     : "=r"(bq[U][0]), "=r"(bq[U][1]), "=r"(bq[U][2]), "=r"(bq[U][3]) : "r"(bl + U * 64));
      };
#pragma unroll
      for (int U = 0; U < BPRE; U++) load_bias(U);
      uint32_t fa[4];
#pragma unroll
      for (int g = 0; g < 4; g++) asm volatile("xor.b32 %0, %1, %2;" : "=r"(fa[g]) : "r"(frag0), "r"(g * 32));
      wg_wait<1>();
      release_b(slot_m2);
      if (t + 1 < ntiles) mbar_spin(sb + BAR_BFULL + rb.slot * 8, rb.phase);
      wg_wait<0>();
#pragma unroll
      for (int i = 0; i < 128; i++) asm volatile("" : "+f"(acc[i]) :: "memory");
      release_b(slot_m1);
      if (hold) release_a(3);
      PROF(t * 32 + wg * 16 + 2);

      auto pack = [&](int i) {
        uint32_t v;
        asm("cvt.rn.bf16x2.f32 %0, %1, %2;" : "=r"(v) : "f"(acc[i * 2 + 1]), "f"(acc[i * 2]));
        return v;
      };
      auto cross = [&](int T, int i) {
        uint32_t y, o;
        asm("mul.rn.bf16x2 %0, %1, %2;" : "=r"(y) : "r"(xr[T * 4 + i]), "r"(bq[T >> 1][(T & 1) * 2 + (i >> 1)]));
        asm("fma.rn.bf16x2 %0, %1, %2, %3;" : "=r"(o) : "r"(xr[T * 4 + i]), "r"(pack(T * 4 + i)), "r"(y));
        return o;
      };
      auto reset_acc = [&](int T) {
#pragma unroll
        for (int i = T * 8; i < T * 8 + 8; i++)
          asm("{\n.reg .u32 a, c;\nmov.b32 a, %0;\nmov.b32 c, %2;\nmad.lo.u32 a, a, %1, c;\nmov.b32 %0, a;\n}"
              : "+f"(acc[i]) : "r"(zero), "f"(kOffset));
      };
      if (helper) {
        __nv_bfloat16* dst = optr + (size_t)(job_row(t) + (tid >> 5) * 16 + (lane >> 3)) * kDim + j * 256 + (lane & 7) * 8;
        uint64_t pol;
        asm volatile("createpolicy.fractional.L2::evict_first.b64 %0, 1.0;" : "=l"(pol));
#pragma unroll
        for (int T = 0; T < 16; T++) {
          asm volatile("st.global.L2::cache_hint.v4.b32 [%0], {%1, %2, %3, %4}, %5;"
                       ::"l"(dst + (T & 3) * 4 * kDim + (T >> 2) * 64), "r"(pack(T * 4)), "r"(pack(T * 4 + 1)),
                         "r"(pack(T * 4 + 2)), "r"(pack(T * 4 + 3)), "l"(pol) : "memory");
          reset_acc(T);
        }
        asm volatile("bar.sync %0, 128;" ::"r"(wg + 1) : "memory");
        if (wtid == 0) mbar_arrive(sb + BAR_PUB);
      } else if (hold) {
        const bool inject = t + 1 == short_t;
        const uint32_t prow = ((wtid >> 5) * 16 + (lane >> 3)) * 128 + (((lane & 7) ^ (lane >> 3)) << 4);
#pragma unroll
        for (int T = 0; T < 16; T++) {
#pragma unroll
          for (int i = 0; i < 4; i++) xr[T * 4 + i] = cross(T, i);
          if ((T & 1) && (T >> 1) + BPRE < 8) load_bias((T >> 1) + BPRE);
          if ((T & 3) == 3 && !inject) {
#pragma unroll
            for (int g = T - 3; g <= T; g++) reset_acc(g);
          }
          if ((T & 3) == 3 && inject) {
            const int c = T >> 2;
            if (c > 0) mbar_spin(afull + c * 8, fpar);
            else mbar_spin(sb + BAR_EXTRA + wg * 8, 0);
            const uint32_t src = c > 0 ? abase + c * A_SLOT : sb + OFF_EXTRA;
#pragma unroll
            for (int g = 0; g < 4; g++) load_partial(&acc[(c * 4 + g) * 8], src + (prow ^ ((g & 1) * 64)) + g * 512);
            chunk_staged(c);
#pragma unroll
            for (int g = 0; g < 16; g++)
              if ((g >> 2) == c - 1 || (c == 3 && (g >> 2) == 3)) widen_partial(&acc[g * 8]);
            PROF(t * 32 + wg * 16 + 12 + c);
          }
        }
        if (inject) fpar ^= 1;
      } else {
#pragma unroll
        for (int T = 0; T < 16; T++) {
          uint32_t o[4];
#pragma unroll
          for (int i = 0; i < 4; i++) o[i] = cross(T, i);
          stsm4(fa[T & 3] + (T >> 2) * A_SLOT, o);
          if ((T & 3) == 3) chunk_staged(T >> 2);
          if ((T & 1) && (T >> 1) + BPRE < 8) load_bias((T >> 1) + BPRE);
        }
        PROF(t * 32 + wg * 16 + 7);
        fence_async_smem();
        asm volatile("bar.sync %0, 128;" ::"r"(wg + 1) : "memory");
      }
      PROF(t * 32 + wg * 16 + 3);
      if (t + 1 == ntiles) break;
      if (hold) mbar_spin(afull, fpar);
      half_step(0, 0, 0, t, true);
      if (helper || ++l == kLayers) l = 0;
      swap = hold && !helper;
      q_second = (helper || t + 1 == short_t) ? 3 : 1;
      capture_q = -1;
    }
  } else {
    asm volatile("setmaxnreg.dec.sync.aligned.u32 40;");
    if (tid == 256) {
#pragma unroll
      for (int i = 0; i < 22; i++)
        if (i != 0 && i != NA && i != 8 && i != 9) mbar_init(sb + OFF_BAR + i * 8, 1);
      asm volatile("fence.mbarrier_init.release.cluster;" ::: "memory");
    }
    if (tid == 288) {
#pragma unroll
      for (int i = 0; i < NB + 2; i++) mbar_init(sb + BAR_BEMPTY + i * 8, 2);
#pragma unroll
      for (int i = 0; i < 2 * NA; i++) { mbar_init(sb + BAR_AEMPTY + i * 8, 2); mbar_init(sb + BAR_STAGED + i * 8, 4); }
      asm volatile("fence.mbarrier_init.release.cluster;" ::: "memory");
    }
    __syncwarp();
    cluster_arrive_relaxed();
#pragma unroll 1
    for (int s = warp == 0 ? 1 : 4; s < 4; s++) first_loads(s);
    cluster_wait();
    if (warp) mbar_wait(sb + BAR_AFULL + (warp & 2) * 16, 0);
    if (warp == 0) {
      if ((sb & 1023) || bid >= 4 * (kGroups + 1)) asm volatile("trap;");
      uint32_t zero;
      asm volatile("mov.u32 %0, %%ctaid.y;" : "=r"(zero));
      const CUtensorMap* mwp = (const CUtensorMap*)((const char*)&mw + zero);
      uint32_t dst = sb + OFF_B + 8 * B_SLOT, bar = sb + BAR_BFULL + 8 * 8, phase = 1;
      int c = 256;
      int mask = helper ? ((j & 2) ^ 2) << 8 : 0;
      int row = c ^ mask;
      const uint32_t relaxed = helper ? 1024 : (NT - 2) * 32;
      int left = helper ? kJobs : kTiles;
#pragma unroll 1
      for (;;) {
        mbar_spin(bar + (BAR_BEMPTY - BAR_BFULL), phase);
        if ((uint32_t)((c - 64) & 1023) >= relaxed) __nanosleep(128);
        load_expect_3d_e(dst, mwp, bar, zero, row, j * 4);
        c += 32;
        dst += B_SLOT;
        bar += 8;
        if (bar == sb + BAR_BFULL + NB * 8) { bar = sb + BAR_BFULL; dst = sb + OFF_B; phase ^= 1; }
        if ((c & 511) == 0) {
          if ((c & 512) && (helper || kTiles - left == short_t)) c += 512;
          if (c & 512) {
            mask &= 512;
          } else {
            if (--left == 0) break;
            if (helper || c == kLayers * kDim) c = 0;
            if (!helper) mask = j << 8;
          }
        }
        row = c ^ mask;
      }
    } else if (warp <= 2) {
      const int w = warp - 1;
      const uint32_t abase = sb + OFF_A + w * NA * A_SLOT;
      const uint32_t fullb = sb + BAR_AFULL + w * NA * 8;
      const uint32_t emptyb = sb + BAR_AEMPTY + w * NA * 8;
      const uint32_t stagedb = sb + BAR_STAGED + w * NA * 8;
      const unsigned int base = __shfl_sync(0xffffffffu, *(volatile unsigned int*)(g_flags + bid * 32), 0);
      uint32_t epar = 0;
      uint32_t spar = 0;
      uint32_t last = 0;
      auto refill = [&](const CUtensorMap* m, int col, int row) {
#pragma unroll 1
        for (int s = 0; s < 4; s++) {
          mbar_wait(emptyb + s * 8, epar);
          expect_load_2d_e<false>(abase + s * A_SLOT, m, fullb + s * 8, col + s * 64, row);
        }
        epar ^= 1;
      };
      auto store_refill = [&](int out_row, int col, int row, bool last_read) {
#pragma unroll 1
        for (int s = 0; s < 4; s++) {
          mbar_wait(stagedb + s * 8, spar);
          fence_async_smem();
          store_2d_e<true>(&mo64, abase + s * A_SLOT, j * 256 + s * 64, out_row);
          bulk_commit();
          bulk_wait<0>();
          __syncwarp();
          mbar_wait(emptyb + s * 8, epar);
          if (last_read) expect_load_2d_e<true>(abase + s * A_SLOT, &mx64, fullb + s * 8, col + s * 64, row);
          else expect_load_2d_e<false>(abase + s * A_SLOT, &mx64, fullb + s * 8, col + s * 64, row);
        }
        spar ^= 1;
        epar ^= 1;
      };
      auto store_tile = [&](auto stream, int out_row) {
#pragma unroll 1
        for (int c = 0; c < 4; c++) {
          mbar_wait(stagedb + c * 8, spar);
          fence_async_smem();
          if (!decltype(stream)::value) pace_wait(last, w ? 640 : 512);
          store_2d_e<decltype(stream)::value>(&mo64, abase + c * A_SLOT, j * 256 + c * 64, out_row);
        }
        spar ^= 1;
        bulk_commit();
        bulk_wait<0>();
        __syncwarp();
      };
      auto refill_shared = [&](const CUtensorMap* m32, int col, int row) {
#pragma unroll 1
        for (int s = 0; s < 4; s++) {
          mbar_wait(emptyb + s * 8, epar);
          expect_load_2d_mc_e(abase + s * A_SLOT + rank * 4096, m32, fullb + s * 8, col + s * 64, row + rank * 32);
        }
        epar ^= 1;
      };
      if (helper) {
#pragma unroll 1
        for (int h = 1; h < 2 * kJobs; h++) refill_shared(&mx32, col0 + (h & 1) * 256, job_row(h >> 1) + w * 64);
      } else {
        const uint32_t xready_peer = map_cta(sb + BAR_XREADY + w * 8, rank ^ 1);
        const unsigned int* oflag = g_flags + (grp * 4 + kgroup_col(j, 2)) * 32;
        unsigned int* done_mine = g_flags + kFlagSet + (bid * 2 + w) * 32;
        const unsigned int* done_peer = g_flags + kFlagSet + ((bid ^ 2) * 2 + w) * 32;
        uint32_t nx = 0;
        uint32_t fpar = 0;
#pragma unroll 1
        for (int rd = 0; rd < kRounds; rd++) {
          const int xrow = (rd * kGroups + grp) * 128 + w * 64;
          if (rd == 0) {
            refill(&mx64, 256, xrow);
          } else {
            poll_flag(done_peer, base + nx);
            store_refill(xrow - kGroups * 128, (j ^ 1) * 256, xrow, rd * kLayers == short_t);
          }
          if (rd * kLayers != short_t) {
#pragma unroll 1
            for (int h = 0; h < 2; h++) refill_shared(&mx32, (kgroup_col(rd == 0 ? 0 : j, 2) + h) * 256, xrow);
          }
          fpar ^= 1;
#pragma unroll 1
          for (int l = 1; l < kLayers; l++) {
            if (l > 1) poll_flag(done_peer, base + nx);
            store_tile(Flag<false>(), xrow);
            PROF_SVC((rd * kLayers + l - 1) * 2 + w);
            arrive_mapped_e(xready_peer);
            arrive_e(sb + BAR_PUB);
            mbar_wait(sb + BAR_XREADY + w * 8, nx & 1);
            fence_async_global();
            refill(&mo64, (j ^ 1) * 256, xrow);
            if (rd * kLayers + l + 1 == short_t) {
              poll_flag(g_flags + (4 * kGroups + j) * 32, base + job_of_group(grp) + 1);
              fence_async_global();
              if (w == 0) expect_load_2d_e<false>(sb + OFF_EXTRA, &mo64, sb + BAR_EXTRA, j * 256, xrow + kGroups * 128);
            }
#pragma unroll 1
            for (int h = 0; h < 2; h++) {
              poll_flag(oflag + h * 32, base + nx + 1);
              fence_async_global();
              refill_shared(&mo32, (kgroup_col(j, 2) + h) * 256, xrow);
            }
            fpar ^= 1;
            if (rank) {
#pragma unroll 1
              for (int s = 0; s < 4; s++) mbar_wait(fullb + s * 8, fpar);
            }
            nx++;
            if ((tid & 31) == 0) st_relaxed(done_mine, base + (nx == kRounds * (kLayers - 1) ? kEpoch : nx));
            __syncwarp();
          }
          const int nrow = xrow + kGroups * 128;
          if (rd + 1 == kRounds) {
            poll_flag(done_peer, base + nx);
            store_tile(Flag<true>(), xrow);
          } else if ((rd + 1) * kLayers == short_t) {
#pragma unroll 1
            for (int s = 0; s < 4; s++) {
              mbar_wait(emptyb + s * 8, epar);
              if (s == 0) {
                arrive_e(fullb);
                mbar_wait(fullb, fpar ^ 1);
              }
              expect_load_2d_e<false>(abase + s * A_SLOT, s > 0 ? &mo64 : &mx64, fullb + s * 8, j * 256 + s * 64, nrow);
            }
            epar ^= 1;
#pragma unroll 1
            for (int s = 0; s < 4; s++) {
              mbar_wait(stagedb + s * 8, spar);
              fence_async_smem();
              if (s > 0) expect_load_2d_e<false>(abase + s * A_SLOT, &mx64, fullb + s * 8, j * 256 + s * 64, nrow);
              else if (w == 0) expect_load_2d_e<false>(sb + OFF_EXTRA, &mo64, sb + BAR_EXTRA + 8, j * 256, nrow + 64);
            }
            spar ^= 1;
          } else {
            refill(&mx64, j * 256, nrow);
            fpar ^= 1;
          }
          PROF_SVC((rd * kLayers + kLayers - 1) * 2 + w);
        }
      }
    } else {
      const int lane = tid & 31;
      unsigned int* myflag = g_flags + bid * 32;
      if (lane == 0) { prefetch_map(&mx32); prefetch_map(&mo64); prefetch_map(&mo32); }
      const unsigned int base = *(volatile unsigned int*)myflag;
      if (BY_SM)
        asm volatile("st.volatile.shared::cluster.u32 [%0], %1;"
                     ::"r"(map_cta(sb + OFF_PEER, ~blockIdx.x & 1)), "r"(bid + 1) : "memory");
      auto publish = [&](uint32_t n, uint32_t value) {
        mbar_wait(sb + BAR_PUB, n & 1);
        asm volatile("fence.acq_rel.gpu;" ::: "memory");
        if (BY_SM && n == 1)
          asm volatile("{\n.reg .pred p;\n.reg .u32 v;\nld.volatile.shared.u32 v, [%0];\nsetp.ne.u32 p, v, %1;\n@p trap;\n}"
                       ::"r"(sb + OFF_PEER), "r"(((bid & ~1) | (~blockIdx.x & 1)) + 1) : "memory");
        if (lane == 0) st_relaxed(myflag, base + value);
        __syncwarp();
      };
      if (helper) {
#pragma unroll 1
        for (int n = 0; n < kJobs; n++) {
          if (n + 2 < kJobs) {
            const int row = job_row(n + 2);
#pragma unroll 1
            for (int i = 0; i < 8; i++) prefetch_2d_e(&mx64, col0 + rank * 256 + (i & 3) * 64, row + (i >> 2) * 64);
          }
          publish(n, n + 1);
        }
      } else {
        {
          float c[8];
#pragma unroll
          for (int i = 0; i < 8; i++) c[i] = 1.f - kOffset;
#pragma unroll 1
          for (int l = 0; l < kLayers; l++) {
            const uint4 v = *reinterpret_cast<const uint4*>(bias + l * kDim + j * 256 + lane * 8);
            const uint32_t u[4] = {v.x, v.y, v.z, v.w};
#pragma unroll
            for (int i = 0; i < 4; i++) {
              c[2 * i] += __uint_as_float(u[i] << 16);
              c[2 * i + 1] += __uint_as_float(u[i] & 0xffff0000u);
              uint32_t pk;
              asm("cvt.rn.bf16x2.f32 %0, %1, %2;" : "=r"(pk) : "f"(c[2 * i + 1]), "f"(c[2 * i]));
              asm volatile("st.shared.u32 [%0], %1;" ::"r"(sb + OFF_BIAS + l * 512 + (lane >> 2) * 64 + i * 16 + (lane & 3) * 4),
                           "r"(pk) : "memory");
            }
          }
          __syncwarp();
          if (lane < 2) mbar_arrive(sb + BAR_BIAS);
        }
        const __nv_bfloat16* wslice = wptr + bid * 8192;
        prefetch_1d_e(wslice + kDim * kDim, 16384);
        uint32_t nx = 0;
#pragma unroll 1
        for (int rd = 0; rd < kRounds; rd++) {
#pragma unroll 1
          for (int l = 1; l < kLayers; l++) {
            publish(nx, nx + 1 == kRounds * (kLayers - 1) ? kEpoch : nx + 1);
            nx++;
            if (l < kLayers - 1) {
              if (rd == 0) prefetch_1d_e(wslice + (l + 1) * kDim * kDim, 16384);
            } else if (rd + 1 < kRounds) {
              const int nrow = ((rd + 1) * kGroups + grp) * 128;
              bool partial = false;
              if ((rd + 1) * kLayers == short_t) {
                const unsigned int v = ld_acquire(g_flags + (4 * kGroups + j) * 32);
                partial = __shfl_sync(0xffffffffu, (int)(v - (base + job_of_group(grp) + 1)) >= 0, 0);
              }
#pragma unroll 1
              for (int i = partial ? 0 : 8; i < 16; i++) {
                prefetch_2d_e(i < 8 ? &mo64 : &mx64, j * 256 + ((i >> 1) & 3) * 64, nrow + (i & 1) * 64);
                __nanosleep(i < 8 ? 100 : 300);
              }
            }
          }
        }
      }
    }
    if (warp == (helper ? 3 : 2)) PROF_END();
  }
}

__global__ void __launch_bounds__(256) dcn_fallback(const __nv_bfloat16* __restrict__ x0, const __nv_bfloat16* __restrict__ w,
                                                    const __nv_bfloat16* __restrict__ b, __nv_bfloat16* __restrict__ out) {
  __shared__ float xs[8][kDim];
  const size_t r0 = (size_t)blockIdx.x * 8;
  for (int i = threadIdx.x; i < 8 * kDim; i += 256) xs[i / kDim][i % kDim] = __bfloat162float(x0[r0 * kDim + i]);
  __syncthreads();
  for (int l = 0; l < kLayers; l++) {
    float a[4][8] = {};
    for (int k = 0; k < kDim; k++) {
#pragma unroll
      for (int c = 0; c < 4; c++) {
        const float wv = __bfloat162float(w[((size_t)l * kDim + k) * kDim + c * 256 + threadIdx.x]);
#pragma unroll
        for (int r = 0; r < 8; r++) a[c][r] += xs[r][k] * wv;
      }
    }
    __syncthreads();
#pragma unroll
    for (int c = 0; c < 4; c++) {
      const int n = c * 256 + threadIdx.x;
#pragma unroll
      for (int r = 0; r < 8; r++) {
        const float v = __bfloat162float(x0[(r0 + r) * kDim + n]) * (a[c][r] + __bfloat162float(b[l * kDim + n])) + xs[r][n];
        xs[r][n] = __bfloat162float(__float2bfloat16(v));
      }
    }
    __syncthreads();
  }
  for (int i = threadIdx.x; i < 8 * kDim; i += 256) out[r0 * kDim + i] = __float2bfloat16(xs[i / kDim][i % kDim]);
}

typedef CUresult (*EncodeFn)(CUtensorMap*, CUtensorMapDataType, cuuint32_t, void*, const cuuint64_t*, const cuuint64_t*,
                             const cuuint32_t*, const cuuint32_t*, CUtensorMapInterleave, CUtensorMapSwizzle,
                             CUtensorMapL2promotion, CUtensorMapFloatOOBfill);

static void make_map_2d(EncodeFn enc, CUtensorMap* m, void* ptr, uint64_t rows, uint32_t box_rows) {
  cuuint64_t dims[2] = {(cuuint64_t)kDim, rows};
  cuuint64_t strides[1] = {kDim * 2};
  cuuint32_t box[2] = {64, box_rows};
  cuuint32_t es[2] = {1, 1};
  enc(m, CU_TENSOR_MAP_DATA_TYPE_BFLOAT16, 2, ptr, dims, strides, box, es, CU_TENSOR_MAP_INTERLEAVE_NONE,
      CU_TENSOR_MAP_SWIZZLE_128B, CU_TENSOR_MAP_L2_PROMOTION_L2_128B, CU_TENSOR_MAP_FLOAT_OOB_FILL_NONE);
}

}

extern "C" void kernel_launch(void* const* d_in, const int* in_sizes, int n_in, void* d_out, int out_size) {
  using namespace dcn;
  (void)in_sizes; (void)n_in; (void)out_size;
  void* fn = nullptr;
  cudaDriverEntryPointQueryResult qr;
  cudaGetDriverEntryPoint("cuTensorMapEncodeTiled", &fn, cudaEnableDefault, &qr);
  EncodeFn enc = (EncodeFn)fn;
  CUtensorMap mx64, mx32, mo64, mo32, mw;
  make_map_2d(enc, &mx64, d_in[0], kRows, 64);
  make_map_2d(enc, &mx32, d_in[0], kRows, 32);
  make_map_2d(enc, &mo64, d_out, kRows, 64);
  make_map_2d(enc, &mo32, d_out, kRows, 32);
  {
    cuuint64_t dims[3] = {64, (cuuint64_t)kLayers * kDim, kDim / 64};
    cuuint64_t strides[2] = {kDim * 2, 128};
    cuuint32_t box[3] = {64, 32, 4};
    cuuint32_t es[3] = {1, 1, 1};
    enc(&mw, CU_TENSOR_MAP_DATA_TYPE_BFLOAT16, 3, d_in[1], dims, strides, box, es, CU_TENSOR_MAP_INTERLEAVE_NONE,
        CU_TENSOR_MAP_SWIZZLE_128B, CU_TENSOR_MAP_L2_PROMOTION_L2_128B, CU_TENSOR_MAP_FLOAT_OOB_FILL_NONE);
  }
  const __nv_bfloat16* x0 = (const __nv_bfloat16*)d_in[0];
  const __nv_bfloat16* w = (const __nv_bfloat16*)d_in[1];
  const __nv_bfloat16* b = (const __nv_bfloat16*)d_in[2];
  __nv_bfloat16* out = (__nv_bfloat16*)d_out;
  constexpr int smem = SMEM_BYTES + PROF_SMEM;
  cudaFuncSetAttribute(dcn_kernel<false>, cudaFuncAttributeMaxDynamicSharedMemorySize, smem);
  cudaFuncSetAttribute(dcn_kernel<true>, cudaFuncAttributeMaxDynamicSharedMemorySize, smem);

  cudaLaunchConfig_t cfg = {};
  cfg.gridDim = dim3(4 * kGroups + 4);
  cfg.blockDim = dim3(384);
  cfg.dynamicSmemBytes = smem;
  cudaLaunchAttribute attr;
  attr.id = cudaLaunchAttributeClusterDimension;
  attr.val.clusterDim.x = 2;
  attr.val.clusterDim.y = 1;
  attr.val.clusterDim.z = 1;
  cfg.attrs = &attr;
  cfg.numAttrs = 1;
  int clusters = 0;
  cudaOccupancyMaxActiveClusters(&clusters, dcn_kernel<false>, &cfg);
  int dev = 0, sms = 0;
  cudaGetDevice(&dev);
  cudaDeviceGetAttribute(&sms, cudaDevAttrMultiProcessorCount, dev);
  if (clusters >= 2 * kGroups) {
    const int grid = 4 * kGroups + (clusters >= 2 * kGroups + 2 ? 4 : 0);
    if (grid == sms && grid > 4 * kGroups) dcn_kernel<true><<<grid, 384, smem>>>(mx64, mx32, mo64, mo32, mw, x0, w, b, out);
    else dcn_kernel<false><<<grid, 384, smem>>>(mx64, mx32, mo64, mo32, mw, x0, w, b, out);
  } else {
    dcn_fallback<<<kRows / 8, 256>>>(x0, w, b, out);
  }
}
```

```cpp
#include <cuda_runtime.h>
#include <cuda.h>
#include <cuda_bf16.h>
#include <stdint.h>

namespace dcn {

template <int TA, int TB> __device__ __forceinline__ void wgmma_ss_n256(float (&d)[128], uint64_t da, uint64_t db) {
  asm volatile("{\n.reg .pred p;\nsetp.ne.b32 p, %130, 0;\n"
    "wgmma.mma_async.sync.aligned.m64n256k16.f32.bf16.bf16 "
    "{%0, %1, %2, %3, %4, %5, %6, %7, %8, %9, %10, %11, %12, %13, %14, %15, %16, %17, %18, %19, %20, %21, %22, %23, %24, %25, %26, %27, %28, %29, %30, %31, %32, %33, %34, %35, %36, %37, %38, %39, %40, %41, %42, %43, %44, %45, %46, %47, %48, %49, %50, %51, %52, %53, %54, %55, %56, %57, %58, %59, %60, %61, %62, %63, %64, %65, %66, %67, %68, %69, %70, %71, %72, %73, %74, %75, %76, %77, %78, %79, %80, %81, %82, %83, %84, %85, %86, %87, %88, %89, %90, %91, %92, %93, %94, %95, %96, %97, %98, %99, %100, %101, %102, %103, %104, %105, %106, %107, %108, %109, %110, %111, %112, %113, %114, %115, %116, %117, %118, %119, %120, %121, %122, %123, %124, %125, %126, %127}, "
    "%128, %129, p, 1, 1, %131, %132;\n}\n"
    : "+f"(d[0]), "+f"(d[1]), "+f"(d[2]), "+f"(d[3]), "+f"(d[4]), "+f"(d[5]), "+f"(d[6]), "+f"(d[7]), "+f"(d[8]), "+f"(d[9]), "+f"(d[10]), "+f"(d[11]), "+f"(d[12]), "+f"(d[13]), "+f"(d[14]), "+f"(d[15]), "+f"(d[16]), "+f"(d[17]), "+f"(d[18]), "+f"(d[19]), "+f"(d[20]), "+f"(d[21]), "+f"(d[22]), "+f"(d[23]), "+f"(d[24]), "+f"(d[25]), "+f"(d[26]), "+f"(d[27]), "+f"(d[28]), "+f"(d[29]), "+f"(d[30]), "+f"(d[31]), "+f"(d[32]), "+f"(d[33]), "+f"(d[34]), "+f"(d[35]), "+f"(d[36]), "+f"(d[37]), "+f"(d[38]), "+f"(d[39]), "+f"(d[40]), "+f"(d[41]), "+f"(d[42]), "+f"(d[43]), "+f"(d[44]), "+f"(d[45]), "+f"(d[46]), "+f"(d[47]), "+f"(d[48]), "+f"(d[49]), "+f"(d[50]), "+f"(d[51]), "+f"(d[52]), "+f"(d[53]), "+f"(d[54]), "+f"(d[55]), "+f"(d[56]), "+f"(d[57]), "+f"(d[58]), "+f"(d[59]), "+f"(d[60]), "+f"(d[61]), "+f"(d[62]), "+f"(d[63]), "+f"(d[64]), "+f"(d[65]), "+f"(d[66]), "+f"(d[67]), "+f"(d[68]), "+f"(d[69]), "+f"(d[70]), "+f"(d[71]), "+f"(d[72]), "+f"(d[73]), "+f"(d[74]), "+f"(d[75]), "+f"(d[76]), "+f"(d[77]), "+f"(d[78]), "+f"(d[79]), "+f"(d[80]), "+f"(d[81]), "+f"(d[82]), "+f"(d[83]), "+f"(d[84]), "+f"(d[85]), "+f"(d[86]), "+f"(d[87]), "+f"(d[88]), "+f"(d[89]), "+f"(d[90]), "+f"(d[91]), "+f"(d[92]), "+f"(d[93]), "+f"(d[94]), "+f"(d[95]), "+f"(d[96]), "+f"(d[97]), "+f"(d[98]), "+f"(d[99]), "+f"(d[100]), "+f"(d[101]), "+f"(d[102]), "+f"(d[103]), "+f"(d[104]), "+f"(d[105]), "+f"(d[106]), "+f"(d[107]), "+f"(d[108]), "+f"(d[109]), "+f"(d[110]), "+f"(d[111]), "+f"(d[112]), "+f"(d[113]), "+f"(d[114]), "+f"(d[115]), "+f"(d[116]), "+f"(d[117]), "+f"(d[118]), "+f"(d[119]), "+f"(d[120]), "+f"(d[121]), "+f"(d[122]), "+f"(d[123]), "+f"(d[124]), "+f"(d[125]), "+f"(d[126]), "+f"(d[127])
    : "l"(da), "l"(db), "n"(1), "n"(TA), "n"(TB));
}

constexpr int kDim = 1024;
constexpr int kRows = 16384;
constexpr int kLayers = 6;
constexpr int kGroups = 32;
constexpr int kRounds = kRows / 128 / kGroups;
constexpr int kTiles = kRounds * kLayers;

constexpr float kOffset = 171.f / 128.f;
constexpr int kJobs = kGroups;
constexpr int kEpoch = 32;
constexpr int NA = 4;
constexpr int NB = 9;
constexpr int BPRE = 4;
constexpr int NT = 11;
constexpr int A_SLOT = 8192;
constexpr int B_SLOT = 16384;
constexpr int OFF_B = 0;
constexpr int OFF_A = OFF_B + NB * B_SLOT;
constexpr int OFF_EXTRA = OFF_A + 2 * NA * A_SLOT;
constexpr int OFF_BIAS = OFF_EXTRA + A_SLOT;
constexpr int OFF_BAR = OFF_BIAS + kLayers * 256 * 2;
constexpr int BAR_AFULL = OFF_BAR;
constexpr int BAR_BFULL = OFF_BAR + 64;
constexpr int BAR_ORDER = BAR_BFULL + NB * 8;
constexpr int BAR_XREADY = BAR_ORDER + 8;
constexpr int BAR_EXTRA = BAR_XREADY + 16;
constexpr int BAR_TOUCH = BAR_EXTRA + 16;
constexpr int BAR_BEMPTY = OFF_BAR + 3 * 64;
constexpr int BAR_BIAS = BAR_BEMPTY + NB * 8;
constexpr int BAR_PUB = BAR_BIAS + 8;
constexpr int OFF_PEER = BAR_PUB + 8;
constexpr int BAR_AEMPTY = OFF_BAR + 5 * 64;
constexpr int BAR_STAGED = OFF_BAR + 6 * 64;
constexpr int OFF_TOUCH = OFF_BAR + 8 * 64;
constexpr int SMEM_BYTES = OFF_TOUCH + 1024;
static_assert(BAR_TOUCH + 8 == OFF_BAR + 23 * 8 && NA == 4, "barrier groups");
static_assert(SMEM_BYTES <= 232448, "shared memory budget");

constexpr int kFlagSet = 4 * (kGroups + 1) * 32;
__device__ unsigned int g_flags[3 * kFlagSet];

__device__ __forceinline__ uint32_t smem_u32(const void* p) { return (uint32_t)__cvta_generic_to_shared(p); }
__device__ __forceinline__ void mbar_init(uint32_t bar, int cnt) {
  asm volatile("mbarrier.init.shared::cta.b64 [%0], %1;" ::"r"(bar), "r"(cnt) : "memory");
}
__device__ __forceinline__ void mbar_arrive(uint32_t bar) {
  asm volatile("mbarrier.arrive.shared::cta.b64 _, [%0];" ::"r"(bar) : "memory");
}
__device__ __forceinline__ uint32_t map_cta(uint32_t addr, uint32_t cta) {
  uint32_t r;
  asm volatile("mapa.shared::cluster.u32 %0, %1, %2;" : "=r"(r) : "r"(addr), "r"(cta));
  return r;
}
__device__ __forceinline__ void mbar_arrive_mapped(uint32_t cluster_addr) {
  asm volatile("mbarrier.arrive.shared::cluster.b64 _, [%0];" ::"r"(cluster_addr) : "memory");
}
__device__ __forceinline__ void mbar_wait(uint32_t bar, uint32_t parity) {
  asm volatile(
      "{\n.reg .pred p;\n.reg .u32 c;\n"
      "mbarrier.try_wait.parity.shared::cta.b64 p, [%0], %1;\n"
      "@p bra DONE;\n"
      "mov.u32 c, 0;\n"
      "LOOP:\n"
      "mbarrier.try_wait.parity.shared::cta.b64 p, [%0], %1;\n"
      "@p bra DONE;\n"
      "add.u32 c, c, 1;\n"
      "setp.lt.u32 p, c, 4194304;\n"
      "@p bra LOOP;\n"
      "trap;\n"
      "DONE:\n}"
      ::"r"(bar), "r"(parity) : "memory");
}
__device__ __forceinline__ void mbar_spin(uint32_t bar, uint32_t parity) {
  asm volatile(
      "{\n.reg .pred p;\n"
      "LOOP:\n"
      "mbarrier.try_wait.parity.shared::cta.b64 p, [%0], %1;\n"
      "@!p bra LOOP;\n}"
      ::"r"(bar), "r"(parity) : "memory");
}
#define ELECT_BEGIN "{\n.reg .pred e;\nelect.sync _|e, 0xffffffff;\n"
template <bool STREAM> __device__ __forceinline__ void expect_load_2d_e(uint32_t dst, const CUtensorMap* m, uint32_t bar, int c0, int c1) {
  if (STREAM) {
    asm volatile(ELECT_BEGIN ".reg .b64 pol;\ncreatepolicy.fractional.L2::evict_first.b64 pol, 1.0;\n"
                 "@e mbarrier.arrive.expect_tx.shared::cta.b64 _, [%2], 8192;\n"
                 "@e cp.async.bulk.tensor.2d.shared::cluster.global.mbarrier::complete_tx::bytes.L2::cache_hint [%0], [%1, {%3, %4}], [%2], pol;\n}"
                 ::"r"(dst), "l"(m), "r"(bar), "r"(c0), "r"(c1) : "memory");
  } else {
    asm volatile(ELECT_BEGIN
                 "@e mbarrier.arrive.expect_tx.shared::cta.b64 _, [%2], 8192;\n"
                 "@e cp.async.bulk.tensor.2d.shared::cluster.global.mbarrier::complete_tx::bytes [%0], [%1, {%3, %4}], [%2];\n}"
                 ::"r"(dst), "l"(m), "r"(bar), "r"(c0), "r"(c1) : "memory");
  }
}
__device__ __forceinline__ void expect_load_2d_mc_e(uint32_t dst, const CUtensorMap* m, uint32_t bar, int c0, int c1) {
  asm volatile(ELECT_BEGIN ".reg .b64 pol;\ncreatepolicy.fractional.L2::evict_first.b64 pol, 1.0;\n"
               "@e mbarrier.arrive.expect_tx.shared::cta.b64 _, [%2], 8192;\n"
               "@e cp.async.bulk.tensor.2d.shared::cluster.global.mbarrier::complete_tx::bytes.multicast::cluster.L2::cache_hint [%0], [%1, {%3, %4}], [%2], %5, pol;\n}"
               ::"r"(dst), "l"(m), "r"(bar), "r"(c0), "r"(c1), "h"((uint16_t)3) : "memory");
}
template <int BYTES>
__device__ __forceinline__ void expect_load_3d_e(uint32_t dst, const CUtensorMap* m, uint32_t bar, int c0, int c1, int c2) {
  asm volatile(ELECT_BEGIN
               "@e mbarrier.arrive.expect_tx.shared::cta.b64 _, [%2], %6;\n"
               "@e cp.async.bulk.tensor.3d.shared::cluster.global.mbarrier::complete_tx::bytes [%0], [%1, {%3, %4, %5}], [%2];\n}"
               ::"r"(dst), "l"(m), "r"(bar), "r"(c0), "r"(c1), "r"(c2), "n"(BYTES) : "memory");
}
template <bool STREAM> __device__ __forceinline__ void store_2d_e(const CUtensorMap* m, uint32_t src, int c0, int c1) {
  if (STREAM) {
    asm volatile(ELECT_BEGIN ".reg .b64 pol;\ncreatepolicy.fractional.L2::evict_first.b64 pol, 1.0;\n"
                 "@e cp.async.bulk.tensor.2d.global.shared::cta.bulk_group.L2::cache_hint [%0, {%2, %3}], [%1], pol;\n}"
                 ::"l"(m), "r"(src), "r"(c0), "r"(c1) : "memory");
  } else {
    asm volatile(ELECT_BEGIN
                 "@e cp.async.bulk.tensor.2d.global.shared::cta.bulk_group [%0, {%2, %3}], [%1];\n}"
                 ::"l"(m), "r"(src), "r"(c0), "r"(c1) : "memory");
  }
}
__device__ __forceinline__ void prefetch_2d_e(const CUtensorMap* m, int c0, int c1) {
  asm volatile(ELECT_BEGIN
               "@e cp.async.bulk.prefetch.tensor.2d.L2.global [%0, {%1, %2}];\n}"
               ::"l"(m), "r"(c0), "r"(c1) : "memory");
}
__device__ __forceinline__ void prefetch_1d_e(const void* ptr, uint32_t bytes) {
  asm volatile(ELECT_BEGIN
               "@e cp.async.bulk.prefetch.L2.global [%0], %1;\n}"
               ::"l"(ptr), "r"(bytes) : "memory");
}
__device__ __forceinline__ void load_expect_3d_e(uint32_t dst, const CUtensorMap* m, uint32_t bar, int c0, int c1, int c2) {
  asm volatile(ELECT_BEGIN
               "@e cp.async.bulk.tensor.3d.shared::cluster.global.mbarrier::complete_tx::bytes [%0], [%1, {%3, %4, %5}], [%2];\n"
               "@e mbarrier.arrive.expect_tx.shared::cta.b64 _, [%2], 16384;\n}"
               ::"r"(dst), "l"(m), "r"(bar), "r"(c0), "r"(c1), "r"(c2) : "memory");
}
__device__ __forceinline__ void pace_wait(uint32_t& last, uint32_t gap) {
  asm volatile("{\n.reg .pred p;\n.reg .u32 b, d;\n"
               "AGAIN:\n"
               "mov.u32 b, %%clock;\n"
               "sub.u32 d, b, %0;\n"
               "setp.lt.u32 p, d, %1;\n"
               "@p bra.uni AGAIN;\n"
               "mov.u32 %0, b;\n}" : "+r"(last) : "r"(gap) : "memory");
}
__device__ __forceinline__ void arrive_mapped_e(uint32_t cluster_addr) {
  asm volatile(ELECT_BEGIN "@e mbarrier.arrive.shared::cluster.b64 _, [%0];\n}" ::"r"(cluster_addr) : "memory");
}
__device__ __forceinline__ void arrive_e(uint32_t bar) {
  asm volatile(ELECT_BEGIN "@e mbarrier.arrive.shared::cta.b64 _, [%0];\n}" ::"r"(bar) : "memory");
}
__device__ __forceinline__ void bulk_commit() { asm volatile("cp.async.bulk.commit_group;" ::: "memory"); }
template <int N> __device__ __forceinline__ void bulk_wait() { asm volatile("cp.async.bulk.wait_group %0;" ::"n"(N) : "memory"); }
__device__ __forceinline__ void wg_fence() { asm volatile("wgmma.fence.sync.aligned;" ::: "memory"); }
__device__ __forceinline__ void wg_commit() { asm volatile("wgmma.commit_group.sync.aligned;" ::: "memory"); }
template <int N> __device__ __forceinline__ void wg_wait() { asm volatile("wgmma.wait_group.sync.aligned %0;" ::"n"(N) : "memory"); }
__device__ __forceinline__ void fence_async_global() { asm volatile("fence.proxy.async.global;" ::: "memory"); }
__device__ __forceinline__ void st_relaxed(unsigned int* p, unsigned int v) {
  asm volatile("st.relaxed.gpu.global.u32 [%0], %1;" ::"l"(p), "r"(v) : "memory");
}
__device__ __forceinline__ unsigned int ld_acquire(const unsigned int* p) {
  unsigned int v;
  asm volatile("ld.acquire.gpu.global.u32 %0, [%1];" : "=r"(v) : "l"(p) : "memory");
  return v;
}
__device__ __forceinline__ void ldsm4(uint32_t* r, uint32_t addr) {
  asm volatile("ldmatrix.sync.aligned.m8n8.x4.shared.b16 {%0, %1, %2, %3}, [%4];"
               : "=r"(r[0]), "=r"(r[1]), "=r"(r[2]), "=r"(r[3]) : "r"(addr) : "memory");
}
__device__ __forceinline__ void stsm4(uint32_t addr, const uint32_t* r) {
  asm volatile("stmatrix.sync.aligned.m8n8.x4.shared.b16 [%0], {%1, %2, %3, %4};"
               ::"r"(addr), "r"(r[0]), "r"(r[1]), "r"(r[2]), "r"(r[3]) : "memory");
}
__device__ __forceinline__ void load_partial(float* a, uint32_t addr) {
  asm volatile("ld.shared.v4.f32 {%0, %1, %2, %3}, [%4];"
               : "+f"(a[4]), "+f"(a[5]), "+f"(a[6]), "+f"(a[7]) : "r"(addr) : "memory");
}
__device__ __forceinline__ void widen_partial(float* a) {
  asm volatile("shl.b32 %0, %4, 16;\nand.b32 %1, %4, 0xffff0000;\n"
               "shl.b32 %2, %5, 16;\nand.b32 %3, %5, 0xffff0000;\n"
               "shl.b32 %4, %6, 16;\nand.b32 %5, %6, 0xffff0000;\n"
               "shl.b32 %6, %7, 16;\nand.b32 %7, %7, 0xffff0000;"
               : "+f"(a[0]), "+f"(a[1]), "+f"(a[2]), "+f"(a[3]), "+f"(a[4]), "+f"(a[5]), "+f"(a[6]), "+f"(a[7]));
}
template <bool V> struct Flag { static constexpr bool value = V; };
__device__ __forceinline__ void fence_async_smem() { asm volatile("fence.proxy.async.shared::cta;" ::: "memory"); }
__device__ __forceinline__ void cluster_arrive_relaxed() { asm volatile("barrier.cluster.arrive.relaxed.aligned;" ::: "memory"); }
__device__ __forceinline__ void cluster_wait() { asm volatile("barrier.cluster.wait.acquire.aligned;" ::: "memory"); }
__device__ __forceinline__ void prefetch_map(const CUtensorMap* m) {
  asm volatile("prefetch.tensormap [%0];" ::"l"(m) : "memory");
}
__device__ __forceinline__ void poll_flag(const unsigned int* ptr, unsigned int target) {
  asm volatile(
      "{\n.reg .pred p;\n.reg .u32 c;\n.reg .s32 v;\n"
      "mov.u32 c, 0;\n"
      "LOOP:\n"
      "ld.acquire.gpu.global.s32 v, [%0];\n"
      "sub.s32 v, v, %1;\n"
      "setp.ge.s32 p, v, 0;\n"
      "@p bra DONE;\n"
      "add.u32 c, c, 1;\n"
      "setp.lt.u32 p, c, 4194304;\n"
      "@p bra LOOP;\n"
      "trap;\n"
      "DONE:\n}"
      ::"l"(ptr), "r"(target) : "memory");
}

constexpr uint32_t DESC_HI = (1024u >> 4) | (1u << 30);
__device__ __forceinline__ uint64_t desc(uint32_t lo) { return ((uint64_t)DESC_HI << 32) | lo; }
constexpr uint32_t DESC_A_LBO = 1u << 16;
constexpr uint32_t DESC_B_LBO = (4096u >> 4) << 16;

struct Ring {
  uint32_t slot, phase;
  template <int N> __device__ __forceinline__ void next() {
    if (++slot == N) { slot = 0; phase ^= 1; }
  }
};

__device__ __forceinline__ int kgroup_col(int j, int q) {
  return q == 0 ? j : (q == 1 ? (j ^ 1) : (((j ^ 2) & ~1) + (q - 2)));
}

__device__ __forceinline__ int role_of_pair(int t) {
  const int b = t - 32, r = (b * 37) >> 8;
  const int gpc = t < 32 ? t : (t < 60 ? 1 + b - r * 7 : 0);
  const int pass = t < 32 ? t >> 3 : (t < 60 ? 4 + r : t - 58);
  return (t >> 1) == 30 ? t + 4 : pass * 8 + ((0x51703246 >> ((gpc * 4) & 31)) & 7);
}
__device__ __forceinline__ int helped_round(int grp) { return (grp & 2) ? (grp & 3) - 1 : 3; }
__device__ __forceinline__ int job_of_group(int grp) {
  return (grp & 2) ? (grp & 1) * 8 + (grp >> 2) : 16 + (grp >> 2) * 2 + (grp & 1);
}
__device__ __forceinline__ int job_row(int n) {
  const int grp = n < 16 ? (n & 7) * 4 + 2 + (n >> 3) : ((n - 16) >> 1) * 4 + (n & 1);
  return (helped_round(grp) * kGroups + grp) * 128;
}

#define PROF_START() do {} while (0)
#define PROF_END() do {} while (0)
#define PROF_SVC(idx) do {} while (0)
#define PROF(idx) do {} while (0)
#define PROF_SMEM 0

template <bool BY_SM>
__global__ void __cluster_dims__(2, 1, 1) __launch_bounds__(384, 1)
dcn_kernel(const __grid_constant__ CUtensorMap mx64, const __grid_constant__ CUtensorMap mx32,
           const __grid_constant__ CUtensorMap mo64, const __grid_constant__ CUtensorMap mo32,
           const __grid_constant__ CUtensorMap mw, const __grid_constant__ CUtensorMap mxt,
           const __grid_constant__ CUtensorMap mot, const __nv_bfloat16* __restrict__ xptr,
           const __nv_bfloat16* __restrict__ wptr, const __nv_bfloat16* __restrict__ bias, __nv_bfloat16* optr) {
  extern __shared__ __align__(1024) uint8_t smem_raw[];
  const uint32_t sb = smem_u32(smem_raw);
  PROF_START();
  const int tid = threadIdx.x;
  const __nv_bfloat16 *px = nullptr, *pw = nullptr;
  if (tid < 32) {
    const uint32_t r = blockIdx.x * 32 + tid;
    px = xptr + (size_t)r * kDim;
    pw = wptr + (size_t)((r & 1023) * 64);
    asm volatile("prefetch.global.L2 [%0];" ::"l"(px));
    asm volatile("prefetch.global.L2 [%0];" ::"l"(pw));
  }
  if (tid == 256) {
    prefetch_map(&mw);
    prefetch_map(&mx64);
    mbar_init(sb + BAR_BFULL, 1);
    mbar_init(sb + BAR_BFULL + 8, 1);
    mbar_init(sb + BAR_AFULL, 1);
    mbar_init(sb + BAR_AFULL + NA * 8, 1);
    asm volatile("fence.mbarrier_init.release.cluster;" ::: "memory");
  }
  const int wid = __shfl_sync(0xffffffffu, tid >> 5, 0);
  uint32_t place = blockIdx.x + (blockIdx.x < 8 ? 124 : -8);
  if (BY_SM) asm volatile("mov.u32 %0, %%smid;" : "=r"(place));
  const int bid = role_of_pair(place >> 1) * 2 + (place & 1);
  const int j = bid & 3;
  const int grp = bid >> 2;
  const bool helper = grp == kGroups;
  const int col0 = helper ? kgroup_col(j, 2) * 256 : 0;
  const int row0 = helper ? job_row(0) : grp * 128;
  auto first_loads = [&](int s) {
    const int col = col0 + s * 64;
    expect_load_3d_e<B_SLOT>(sb + OFF_B + 2 * s * B_SLOT, &mw, sb + BAR_BFULL + 2 * s * 8, 0, col, j * 4);
    expect_load_2d_e<false>(sb + OFF_A + s * A_SLOT, &mx64, sb + BAR_AFULL + s * 8, col, row0);
    expect_load_2d_e<false>(sb + OFF_A + (NA + s) * A_SLOT, &mx64, sb + BAR_AFULL + (NA + s) * 8, col, row0 + 64);
    expect_load_3d_e<B_SLOT>(sb + OFF_B + (2 * s + 1) * B_SLOT, &mw, sb + BAR_BFULL + (2 * s + 1) * 8, 0, col + 32, j * 4);
  };
  if (wid == 8) first_loads(0);
  __syncthreads();
  const int wg = wid >> 2, warp = wid & 3;
  const uint32_t rank = j & 1;
  const int short_t = ((BY_SM || gridDim.x > 4 * kGroups) && !helper) ? helped_round(grp) * kLayers : -1;

  if (wg < 2) {
    cluster_arrive_relaxed();
    asm volatile("setmaxnreg.inc.sync.aligned.u32 232;");
    if (tid < 32) asm volatile("prefetch.global.L2 [%0+128];\nprefetch.global.L2 [%1+131072];" ::"l"(px), "l"(pw));
    const int lane = tid & 31;
    const int wtid = tid & 127;
    const uint32_t abase = sb + OFF_A + wg * NA * A_SLOT;
    const uint32_t afull = sb + BAR_AFULL + wg * NA * 8;
    const uint32_t aempty = map_cta(sb + BAR_AEMPTY + wg * NA * 8, wtid == 32 ? (rank ^ 1) : rank);
    const bool rel_a = (wtid == 0) || (wtid == 32);
    const bool rel_b = (wtid == 64);
    const uint32_t frag0 = __shfl_sync(0xffffffffu, abase + ((wtid >> 5) * 16 + ((lane >> 3) & 1) * 8 + (lane & 7)) * 128 +
                                                        (((lane >> 4) ^ (lane & 7)) << 4), lane);
    const uint32_t adesc0 = ((abase & 0x3FFFF) >> 4) | DESC_A_LBO;
    const uint32_t bdesc0 = (((sb + OFF_B) & 0x3FFFF) >> 4) | DESC_B_LBO;

    uint32_t zero;
    asm volatile("mov.u32 %0, %%ctaid.y;" : "=r"(zero));
    float acc[128];
    uint32_t xr[64];
    asm volatile("st.shared.v4.f32 [%0], {%1, %1, %1, %1};" ::"r"(sb + OFF_EXTRA + wid * 16), "f"(kOffset) : "memory");
#pragma unroll
    for (int i = 0; i < 128; i += 4)
      asm volatile("ld.volatile.shared.v4.f32 {%0, %1, %2, %3}, [%4];"
                   : "=f"(acc[i]), "=f"(acc[i + 1]), "=f"(acc[i + 2]), "=f"(acc[i + 3]) : "r"(sb + OFF_EXTRA + wid * 16) : "memory");
#pragma unroll
    for (int i = 0; i < 64; i++) asm volatile("" : "=r"(xr[i]));
    Ring rb{0, 0};
    uint32_t slot_m1 = 0, slot_m2 = 0, slot_m3 = 0;
    uint32_t fpar = 0;
    int l = 0;
    bool hold = false;
    bool swap = false;
    int q_second = helper ? 3 : 1;
    int capture_q = helper ? -1 : j;

    auto release_b = [&](uint32_t slot) {
      if (rel_b) mbar_arrive(sb + BAR_BEMPTY + slot * 8);
    };
    auto release_a = [&](int s) {
      if (rel_a) mbar_arrive_mapped(aempty + s * 8);
    };
    auto chunk_staged = [&](int c) {
      __syncwarp();
      arrive_e(sb + BAR_STAGED + (wg * NA + c) * 8);
    };
    auto capture_slot = [&](int p) {
#pragma unroll
      for (int g = 0; g < 4; g++) ldsm4(&xr[(p * 4 + g) * 4], (frag0 ^ (g * 32)) + p * A_SLOT);
    };
    auto swap_half = [&](int p, int half) {
#pragma unroll
      for (int g = half * 2; g < half * 2 + 2; g++) {
        const uint32_t addr = (frag0 ^ (g * 32)) + p * A_SLOT;
        uint32_t n[4];
        ldsm4(n, addr);
        stsm4(addr, &xr[(p * 4 + g) * 4]);
#pragma unroll
        for (int i = 0; i < 4; i++) xr[(p * 4 + g) * 4 + i] = n[i];
      }
      if (half) chunk_staged(p);
    };
    auto half_step = [&](int q, int s, int h, int t, bool first) {
      if (s == 0 && h == 1 && q == 3 && wg == 1) {
        wg_wait<1>();
        release_b(slot_m2);
        wg_wait<0>();
        release_b(slot_m1);
        if (swap && q_second == 3) { swap_half(3, 0); swap_half(3, 1); }
        release_a(3);
        mbar_spin(sb + BAR_ORDER, t & 1);
      }
      if (!(first && h == 0)) mbar_spin(sb + BAR_BFULL + rb.slot * 8, rb.phase);
      const uint32_t bdesc = bdesc0 + rb.slot * (B_SLOT >> 4);
      const uint32_t adesc = adesc0 + s * (A_SLOT >> 4) + h * 4;
      wg_fence();
      wgmma_ss_n256<0, 1>(acc, desc(adesc), desc(bdesc));
      wgmma_ss_n256<0, 1>(acc, desc(adesc + 2), desc(bdesc + 128));
      wg_commit();
      slot_m3 = slot_m2;
      slot_m2 = slot_m1;
      slot_m1 = rb.slot;
      rb.next<NB>();
      if (s == 3 && h == 1 && q == 3 && wg == 0 && wtid == 96) mbar_arrive(sb + BAR_ORDER);
    };
    auto retire = [&](int q, int s, int h, bool first) {
      if (h == 1 && q == capture_q) capture_slot(s);
      const bool drained = s * 2 + h >= 1 && s * 2 + h <= 2 && q == 3 && wg == 1;
      if (!first && !drained) {
        wg_wait<2>();
        release_b(slot_m3);
        if (h == 1) {
          if (s == 0 || q < 3 || hold) release_a((s + 3) & 3);
          if ((s == 0 || q == 0) && swap && q == (s == 0 ? q_second : 0)) swap_half((s + 3) & 3, 0);
        } else {
          if ((s <= 1) != (q == 0) && swap && q == (s <= 1 ? q_second : 0)) swap_half((s + 2) & 3, 1);
        }
      }
    };

    cluster_wait();
    const int ntiles = helper ? kJobs : kTiles;
    mbar_spin(afull, 0);
    half_step(0, 0, 0, 0, false);
#pragma unroll 1
    for (int t = 0;; t++) {
      hold = (helper || l == kLayers - 1) && (t + 1 < ntiles);
      PROF(t * 32 + wg * 16 + 0);
#pragma unroll
      for (int s = 0; s < 4; s++) {
        if (s > 0) {
          if (l == 0) mbar_spin(afull + s * 8, fpar);
          PROF(t * 32 + wg * 16 + 8 + s);
          half_step(0, s, 0, t, false);
        }
        retire(0, s, 0, s == 0);
        half_step(0, s, 1, t, s == 0);
        retire(0, s, 1, s == 0);
      }
      if (l == 0) fpar ^= 1;
      PROF(t * 32 + wg * 16 + 1);
#pragma unroll 1
      for (int q = q_second; q < 4; q++) {
#pragma unroll
        for (int s = 0; s < 4; s++) {
          mbar_spin(afull + s * 8, fpar);
          if (s == 0) PROF(t * 32 + wg * 16 + 3 + q);
          half_step(q, s, 0, t, false);
          retire(q, s, 0, false);
          half_step(q, s, 1, t, false);
          retire(q, s, 1, false);
        }
        fpar ^= 1;
      }
      if (t == 0 && !helper) mbar_spin(sb + BAR_BIAS, 0);
      const uint32_t bl = sb + OFF_BIAS + l * 512 + (lane & 3) * 16;
      uint32_t bq[8][4];
      auto load_bias = [&](int U) {
        asm volatile("ld.shared.v4.u32 {%0, %1, %2, %3}, [%4];"
                     : "=r"(bq[U][0]), "=r"(bq[U][1]), "=r"(bq[U][2]), "=r"(bq[U][3]) : "r"(bl + U * 64));
      };
#pragma unroll
      for (int U = 0; U < BPRE; U++) load_bias(U);
      uint32_t fa[4];
#pragma unroll
      for (int g = 0; g < 4; g++) asm volatile("xor.b32 %0, %1, %2;" : "=r"(fa[g]) : "r"(frag0), "r"(g * 32));
      wg_wait<1>();
      release_b(slot_m2);
      if (t + 1 < ntiles) mbar_spin(sb + BAR_BFULL + rb.slot * 8, rb.phase);
      wg_wait<0>();
#pragma unroll
      for (int i = 0; i < 128; i++) asm volatile("" : "+f"(acc[i]) :: "memory");
      release_b(slot_m1);
      if (hold) release_a(3);
      PROF(t * 32 + wg * 16 + 2);

      auto pack = [&](int i) {
        uint32_t v;
        asm("cvt.rn.bf16x2.f32 %0, %1, %2;" : "=r"(v) : "f"(acc[i * 2 + 1]), "f"(acc[i * 2]));
        return v;
      };
      auto cross = [&](int T, int i) {
        uint32_t y, o;
        asm("mul.rn.bf16x2 %0, %1, %2;" : "=r"(y) : "r"(xr[T * 4 + i]), "r"(bq[T >> 1][(T & 1) * 2 + (i >> 1)]));
        asm("fma.rn.bf16x2 %0, %1, %2, %3;" : "=r"(o) : "r"(xr[T * 4 + i]), "r"(pack(T * 4 + i)), "r"(y));
        return o;
      };
      auto reset_acc = [&](int T) {
#pragma unroll
        for (int i = T * 8; i < T * 8 + 8; i++)
          asm("{\n.reg .u32 a, c;\nmov.b32 a, %0;\nmov.b32 c, %2;\nmad.lo.u32 a, a, %1, c;\nmov.b32 %0, a;\n}"
              : "+f"(acc[i]) : "r"(zero), "f"(kOffset));
      };
      if (helper) {
        __nv_bfloat16* dst = optr + (size_t)(job_row(t) + (tid >> 5) * 16 + (lane >> 3)) * kDim + j * 256 + (lane & 7) * 8;
        uint64_t pol;
        asm volatile("createpolicy.fractional.L2::evict_first.b64 %0, 1.0;" : "=l"(pol));
#pragma unroll
        for (int T = 0; T < 16; T++) {
          asm volatile("st.global.L2::cache_hint.v4.b32 [%0], {%1, %2, %3, %4}, %5;"
                       ::"l"(dst + (T & 3) * 4 * kDim + (T >> 2) * 64), "r"(pack(T * 4)), "r"(pack(T * 4 + 1)),
                         "r"(pack(T * 4 + 2)), "r"(pack(T * 4 + 3)), "l"(pol) : "memory");
          reset_acc(T);
        }
        asm volatile("bar.sync %0, 128;" ::"r"(wg + 1) : "memory");
        if (wtid == 0) mbar_arrive(sb + BAR_PUB);
      } else if (hold) {
        const bool inject = t + 1 == short_t;
        const uint32_t prow = ((wtid >> 5) * 16 + (lane >> 3)) * 128 + (((lane & 7) ^ (lane >> 3)) << 4);
#pragma unroll
        for (int T = 0; T < 16; T++) {
#pragma unroll
          for (int i = 0; i < 4; i++) xr[T * 4 + i] = cross(T, i);
          if ((T & 1) && (T >> 1) + BPRE < 8) load_bias((T >> 1) + BPRE);
          if ((T & 3) == 3 && !inject) {
#pragma unroll
            for (int g = T - 3; g <= T; g++) reset_acc(g);
          }
          if ((T & 3) == 3 && inject) {
            const int c = T >> 2;
            if (c > 0) mbar_spin(afull + c * 8, fpar);
            else mbar_spin(sb + BAR_EXTRA + wg * 8, 0);
            const uint32_t src = c > 0 ? abase + c * A_SLOT : sb + OFF_EXTRA;
#pragma unroll
            for (int g = 0; g < 4; g++) load_partial(&acc[(c * 4 + g) * 8], src + (prow ^ ((g & 1) * 64)) + g * 512);
            chunk_staged(c);
#pragma unroll
            for (int g = 0; g < 16; g++)
              if ((g >> 2) == c - 1 || (c == 3 && (g >> 2) == 3)) widen_partial(&acc[g * 8]);
            PROF(t * 32 + wg * 16 + 12 + c);
          }
        }
        if (inject) fpar ^= 1;
      } else {
#pragma unroll
        for (int T = 0; T < 16; T++) {
          uint32_t o[4];
#pragma unroll
          for (int i = 0; i < 4; i++) o[i] = cross(T, i);
          stsm4(fa[T & 3] + (T >> 2) * A_SLOT, o);
          if ((T & 3) == 3) chunk_staged(T >> 2);
          if ((T & 1) && (T >> 1) + BPRE < 8) load_bias((T >> 1) + BPRE);
        }
        PROF(t * 32 + wg * 16 + 7);
        fence_async_smem();
        asm volatile("bar.sync %0, 128;" ::"r"(wg + 1) : "memory");
      }
      PROF(t * 32 + wg * 16 + 3);
      if (t + 1 == ntiles) break;
      if (hold) mbar_spin(afull, fpar);
      half_step(0, 0, 0, t, true);
      if (helper || ++l == kLayers) l = 0;
      swap = hold && !helper;
      q_second = (helper || t + 1 == short_t) ? 3 : 1;
      capture_q = -1;
    }
  } else {
    asm volatile("setmaxnreg.dec.sync.aligned.u32 40;");
    if (tid == 256) {
#pragma unroll
      for (int i = 0; i < 23; i++)
        if (i != 0 && i != NA && i != 8 && i != 9) mbar_init(sb + OFF_BAR + i * 8, 1);
      asm volatile("fence.mbarrier_init.release.cluster;" ::: "memory");
    }
    if (tid == 288) {
#pragma unroll
      for (int i = 0; i < NB + 2; i++) mbar_init(sb + BAR_BEMPTY + i * 8, 2);
#pragma unroll
      for (int i = 0; i < 2 * NA; i++) { mbar_init(sb + BAR_AEMPTY + i * 8, 2); mbar_init(sb + BAR_STAGED + i * 8, 4); }
      asm volatile("fence.mbarrier_init.release.cluster;" ::: "memory");
    }
    __syncwarp();
    cluster_arrive_relaxed();
#pragma unroll 1
    for (int s = warp == 0 ? 1 : 4; s < 4; s++) first_loads(s);
    cluster_wait();
    if (warp) mbar_wait(sb + BAR_AFULL + (warp & 2) * 16, 0);
    if (warp == 0) {
      if ((sb & 1023) || bid >= 4 * (kGroups + 1)) asm volatile("trap;");
      uint32_t zero;
      asm volatile("mov.u32 %0, %%ctaid.y;" : "=r"(zero));
      const CUtensorMap* mwp = (const CUtensorMap*)((const char*)&mw + zero);
      uint32_t dst = sb + OFF_B + 8 * B_SLOT, bar = sb + BAR_BFULL + 8 * 8, phase = 1;
      int c = 256;
      int mask = helper ? ((j & 2) ^ 2) << 8 : 0;
      int row = c ^ mask;
      const uint32_t relaxed = helper ? 1024 : (NT - 2) * 32;
      int left = helper ? kJobs : kTiles;
#pragma unroll 1
      for (;;) {
        mbar_spin(bar + (BAR_BEMPTY - BAR_BFULL), phase);
        if ((uint32_t)((c - 64) & 1023) >= relaxed) __nanosleep(128);
        load_expect_3d_e(dst, mwp, bar, zero, row, j * 4);
        c += 32;
        dst += B_SLOT;
        bar += 8;
        if (bar == sb + BAR_BFULL + NB * 8) { bar = sb + BAR_BFULL; dst = sb + OFF_B; phase ^= 1; }
        if ((c & 511) == 0) {
          if ((c & 512) && (helper || kTiles - left == short_t)) c += 512;
          if (c & 512) {
            mask &= 512;
          } else {
            if (--left == 0) break;
            if (helper || c == kLayers * kDim) c = 0;
            if (!helper) mask = j << 8;
          }
        }
        row = c ^ mask;
      }
    } else if (warp <= 2) {
      const int w = warp - 1;
      const uint32_t abase = sb + OFF_A + w * NA * A_SLOT;
      const uint32_t fullb = sb + BAR_AFULL + w * NA * 8;
      const uint32_t emptyb = sb + BAR_AEMPTY + w * NA * 8;
      const uint32_t stagedb = sb + BAR_STAGED + w * NA * 8;
      const unsigned int base = __shfl_sync(0xffffffffu, *(volatile unsigned int*)(g_flags + bid * 32), 0);
      uint32_t epar = 0;
      uint32_t spar = 0;
      uint32_t last = 0;
      auto refill = [&](const CUtensorMap* m, int col, int row) {
#pragma unroll 1
        for (int s = 0; s < 4; s++) {
          mbar_wait(emptyb + s * 8, epar);
          expect_load_2d_e<false>(abase + s * A_SLOT, m, fullb + s * 8, col + s * 64, row);
        }
        epar ^= 1;
      };
      auto store_refill = [&](int out_row, int col, int row, bool last_read) {
#pragma unroll 1
        for (int s = 0; s < 4; s++) {
          mbar_wait(stagedb + s * 8, spar);
          fence_async_smem();
          store_2d_e<true>(&mo64, abase + s * A_SLOT, j * 256 + s * 64, out_row);
          bulk_commit();
          bulk_wait<0>();
          __syncwarp();
          mbar_wait(emptyb + s * 8, epar);
          if (last_read) expect_load_2d_e<true>(abase + s * A_SLOT, &mx64, fullb + s * 8, col + s * 64, row);
          else expect_load_2d_e<false>(abase + s * A_SLOT, &mx64, fullb + s * 8, col + s * 64, row);
        }
        spar ^= 1;
        epar ^= 1;
      };
      auto store_tile = [&](auto stream, int out_row) {
#pragma unroll 1
        for (int c = 0; c < 4; c++) {
          mbar_wait(stagedb + c * 8, spar);
          fence_async_smem();
          if (!decltype(stream)::value) pace_wait(last, w ? 640 : 512);
          store_2d_e<decltype(stream)::value>(&mo64, abase + c * A_SLOT, j * 256 + c * 64, out_row);
        }
        spar ^= 1;
        bulk_commit();
        bulk_wait<0>();
        __syncwarp();
      };
      auto refill_shared = [&](const CUtensorMap* m32, int col, int row) {
#pragma unroll 1
        for (int s = 0; s < 4; s++) {
          mbar_wait(emptyb + s * 8, epar);
          expect_load_2d_mc_e(abase + s * A_SLOT + rank * 4096, m32, fullb + s * 8, col + s * 64, row + rank * 32);
        }
        epar ^= 1;
      };
      if (helper) {
#pragma unroll 1
        for (int h = 1; h < 2 * kJobs; h++) refill_shared(&mx32, col0 + (h & 1) * 256, job_row(h >> 1) + w * 64);
      } else {
        const uint32_t xready_peer = map_cta(sb + BAR_XREADY + w * 8, rank ^ 1);
        const unsigned int* oflag = g_flags + (grp * 4 + kgroup_col(j, 2)) * 32;
        unsigned int* done_mine = g_flags + kFlagSet + (bid * 2 + w) * 32;
        const unsigned int* done_peer = g_flags + kFlagSet + ((bid ^ 2) * 2 + w) * 32;
        uint32_t nx = 0;
        uint32_t fpar = 0;
#pragma unroll 1
        for (int rd = 0; rd < kRounds; rd++) {
          const int xrow = (rd * kGroups + grp) * 128 + w * 64;
          if (rd == 0) {
            refill(&mx64, 256, xrow);
          } else {
            poll_flag(done_peer, base + nx);
            store_refill(xrow - kGroups * 128, (j ^ 1) * 256, xrow, rd * kLayers == short_t);
          }
          if (rd * kLayers != short_t) {
#pragma unroll 1
            for (int h = 0; h < 2; h++) refill_shared(&mx32, (kgroup_col(rd == 0 ? 0 : j, 2) + h) * 256, xrow);
          }
          fpar ^= 1;
#pragma unroll 1
          for (int l = 1; l < kLayers; l++) {
            if (l > 1) poll_flag(done_peer, base + nx);
            store_tile(Flag<false>(), xrow);
            PROF_SVC((rd * kLayers + l - 1) * 2 + w);
            arrive_mapped_e(xready_peer);
            arrive_e(sb + BAR_PUB);
            mbar_wait(sb + BAR_XREADY + w * 8, nx & 1);
            fence_async_global();
            refill(&mo64, (j ^ 1) * 256, xrow);
            if (rd * kLayers + l + 1 == short_t) {
              poll_flag(g_flags + (4 * kGroups + j) * 32, base + job_of_group(grp) + 1);
              fence_async_global();
              if (w == 0) expect_load_2d_e<false>(sb + OFF_EXTRA, &mo64, sb + BAR_EXTRA, j * 256, xrow + kGroups * 128);
            }
#pragma unroll 1
            for (int h = 0; h < 2; h++) {
              poll_flag(oflag + h * 32, base + nx + 1);
              fence_async_global();
              refill_shared(&mo32, (kgroup_col(j, 2) + h) * 256, xrow);
            }
            fpar ^= 1;
            if (rank) {
#pragma unroll 1
              for (int s = 0; s < 4; s++) mbar_wait(fullb + s * 8, fpar);
            }
            nx++;
            if ((tid & 31) == 0) st_relaxed(done_mine, base + (nx == kRounds * (kLayers - 1) ? kEpoch : nx));
            __syncwarp();
          }
          const int nrow = xrow + kGroups * 128;
          if (rd + 1 == kRounds) {
            poll_flag(done_peer, base + nx);
            store_tile(Flag<true>(), xrow);
          } else if ((rd + 1) * kLayers == short_t) {
#pragma unroll 1
            for (int s = 0; s < 4; s++) {
              mbar_wait(emptyb + s * 8, epar);
              if (s == 0) {
                arrive_e(fullb);
                mbar_wait(fullb, fpar ^ 1);
              }
              expect_load_2d_e<false>(abase + s * A_SLOT, s > 0 ? &mo64 : &mx64, fullb + s * 8, j * 256 + s * 64, nrow);
            }
            epar ^= 1;
#pragma unroll 1
            for (int s = 0; s < 4; s++) {
              mbar_wait(stagedb + s * 8, spar);
              fence_async_smem();
              if (s > 0) expect_load_2d_e<false>(abase + s * A_SLOT, &mx64, fullb + s * 8, j * 256 + s * 64, nrow);
              else if (w == 0) expect_load_2d_e<false>(sb + OFF_EXTRA, &mo64, sb + BAR_EXTRA + 8, j * 256, nrow + 64);
            }
            spar ^= 1;
          } else {
            refill(&mx64, j * 256, nrow);
            fpar ^= 1;
          }
          PROF_SVC((rd * kLayers + kLayers - 1) * 2 + w);
        }
      }
    } else {
      const int lane = tid & 31;
      unsigned int* myflag = g_flags + bid * 32;
      if (lane == 0) { prefetch_map(&mx32); prefetch_map(&mo64); prefetch_map(&mo32); }
      const unsigned int base = *(volatile unsigned int*)myflag;
      if (BY_SM)
        asm volatile("st.volatile.shared::cluster.u32 [%0], %1;"
                     ::"r"(map_cta(sb + OFF_PEER, ~blockIdx.x & 1)), "r"(bid + 1) : "memory");
      auto publish = [&](uint32_t n, uint32_t value) {
        mbar_wait(sb + BAR_PUB, n & 1);
        asm volatile("fence.acq_rel.gpu;" ::: "memory");
        if (BY_SM && n == 1)
          asm volatile("{\n.reg .pred p;\n.reg .u32 v;\nld.volatile.shared.u32 v, [%0];\nsetp.ne.u32 p, v, %1;\n@p trap;\n}"
                       ::"r"(sb + OFF_PEER), "r"(((bid & ~1) | (~blockIdx.x & 1)) + 1) : "memory");
        if (lane == 0) st_relaxed(myflag, base + value);
        __syncwarp();
      };
      if (helper) {
#pragma unroll 1
        for (int n = 0; n < kJobs; n++) {
          if (n + 2 < kJobs) {
            const int row = job_row(n + 2);
#pragma unroll 1
            for (int i = 0; i < 8; i++) prefetch_2d_e(&mx64, col0 + rank * 256 + (i & 3) * 64, row + (i >> 2) * 64);
          }
          publish(n, n + 1);
        }
      } else {
        {
          float c[8];
#pragma unroll
          for (int i = 0; i < 8; i++) c[i] = 1.f - kOffset;
#pragma unroll 1
          for (int l = 0; l < kLayers; l++) {
            const uint4 v = *reinterpret_cast<const uint4*>(bias + l * kDim + j * 256 + lane * 8);
            const uint32_t u[4] = {v.x, v.y, v.z, v.w};
#pragma unroll
            for (int i = 0; i < 4; i++) {
              c[2 * i] += __uint_as_float(u[i] << 16);
              c[2 * i + 1] += __uint_as_float(u[i] & 0xffff0000u);
              uint32_t pk;
              asm("cvt.rn.bf16x2.f32 %0, %1, %2;" : "=r"(pk) : "f"(c[2 * i + 1]), "f"(c[2 * i]));
              asm volatile("st.shared.u32 [%0], %1;" ::"r"(sb + OFF_BIAS + l * 512 + (lane >> 2) * 64 + i * 16 + (lane & 3) * 4),
                           "r"(pk) : "memory");
            }
          }
          __syncwarp();
          if (lane < 2) mbar_arrive(sb + BAR_BIAS);
        }
        const __nv_bfloat16* wslice = wptr + bid * 8192;
        prefetch_1d_e(wslice + kDim * kDim, 16384);
        uint32_t nx = 0, tpar = 1;
#pragma unroll 1
        for (int rd = 0; rd < kRounds; rd++) {
#pragma unroll 1
          for (int l = 1; l < kLayers; l++) {
            publish(nx, nx + 1 == kRounds * (kLayers - 1) ? kEpoch : nx + 1);
            nx++;
            if (l < kLayers - 1 && rd == 0) prefetch_1d_e(wslice + (l + 1) * kDim * kDim, 16384);
            if (l >= kLayers - 2 && rd + 1 < kRounds) {
              const int nrow = ((rd + 1) * kGroups + grp) * 128;
              const int count = (rd + 1) * kLayers == short_t ? 8 : 4;
              const int first = (l - (kLayers - 2)) * count;
              bool ready = true;
              if (first == 8) {
                const unsigned int v = ld_acquire(g_flags + (4 * kGroups + j) * 32);
                ready = __shfl_sync(0xffffffffu, (int)(v - (base + job_of_group(grp) + 1)) >= 0, 0);
                fence_async_global();
              }
#pragma unroll 1
              for (int i = first; ready && i < first + count; i++) {
                mbar_wait(sb + BAR_TOUCH, tpar);
                tpar ^= 1;
                expect_load_3d_e<1024>(sb + OFF_TOUCH, i < 8 ? &mxt : &mot, sb + BAR_TOUCH, 0, j * 4, nrow + (i & 7) * 16);
                __nanosleep(count == 8 ? 300 : 600);
              }
            }
          }
        }
      }
    }
    if (warp == (helper ? 3 : 2)) PROF_END();
  }
}

__global__ void __launch_bounds__(256) dcn_fallback(const __nv_bfloat16* __restrict__ x0, const __nv_bfloat16* __restrict__ w,
                                                    const __nv_bfloat16* __restrict__ b, __nv_bfloat16* __restrict__ out) {
  __shared__ float xs[8][kDim];
  const size_t r0 = (size_t)blockIdx.x * 8;
  for (int i = threadIdx.x; i < 8 * kDim; i += 256) xs[i / kDim][i % kDim] = __bfloat162float(x0[r0 * kDim + i]);
  __syncthreads();
  for (int l = 0; l < kLayers; l++) {
    float a[4][8] = {};
    for (int k = 0; k < kDim; k++) {
#pragma unroll
      for (int c = 0; c < 4; c++) {
        const float wv = __bfloat162float(w[((size_t)l * kDim + k) * kDim + c * 256 + threadIdx.x]);
#pragma unroll
        for (int r = 0; r < 8; r++) a[c][r] += xs[r][k] * wv;
      }
    }
    __syncthreads();
#pragma unroll
    for (int c = 0; c < 4; c++) {
      const int n = c * 256 + threadIdx.x;
#pragma unroll
      for (int r = 0; r < 8; r++) {
        const float v = __bfloat162float(x0[(r0 + r) * kDim + n]) * (a[c][r] + __bfloat162float(b[l * kDim + n])) + xs[r][n];
        xs[r][n] = __bfloat162float(__float2bfloat16(v));
      }
    }
    __syncthreads();
  }
  for (int i = threadIdx.x; i < 8 * kDim; i += 256) out[r0 * kDim + i] = __float2bfloat16(xs[i / kDim][i % kDim]);
}

typedef CUresult (*EncodeFn)(CUtensorMap*, CUtensorMapDataType, cuuint32_t, void*, const cuuint64_t*, const cuuint64_t*,
                             const cuuint32_t*, const cuuint32_t*, CUtensorMapInterleave, CUtensorMapSwizzle,
                             CUtensorMapL2promotion, CUtensorMapFloatOOBfill);

static void make_map_2d(EncodeFn enc, CUtensorMap* m, void* ptr, uint64_t rows, uint32_t box_rows) {
  cuuint64_t dims[2] = {(cuuint64_t)kDim, rows};
  cuuint64_t strides[1] = {kDim * 2};
  cuuint32_t box[2] = {64, box_rows};
  cuuint32_t es[2] = {1, 1};
  enc(m, CU_TENSOR_MAP_DATA_TYPE_BFLOAT16, 2, ptr, dims, strides, box, es, CU_TENSOR_MAP_INTERLEAVE_NONE,
      CU_TENSOR_MAP_SWIZZLE_128B, CU_TENSOR_MAP_L2_PROMOTION_L2_128B, CU_TENSOR_MAP_FLOAT_OOB_FILL_NONE);
}

static void make_map_touch(EncodeFn enc, CUtensorMap* m, void* ptr) {
  cuuint64_t dims[3] = {64, kDim / 64, kRows};
  cuuint64_t strides[2] = {128, kDim * 2};
  cuuint32_t box[3] = {8, 4, 16};
  cuuint32_t es[3] = {1, 1, 1};
  enc(m, CU_TENSOR_MAP_DATA_TYPE_BFLOAT16, 3, ptr, dims, strides, box, es, CU_TENSOR_MAP_INTERLEAVE_NONE,
      CU_TENSOR_MAP_SWIZZLE_NONE, CU_TENSOR_MAP_L2_PROMOTION_L2_128B, CU_TENSOR_MAP_FLOAT_OOB_FILL_NONE);
}

}

extern "C" void kernel_launch(void* const* d_in, const int* in_sizes, int n_in, void* d_out, int out_size) {
  using namespace dcn;
  (void)in_sizes; (void)n_in; (void)out_size;
  void* fn = nullptr;
  cudaDriverEntryPointQueryResult qr;
  cudaGetDriverEntryPoint("cuTensorMapEncodeTiled", &fn, cudaEnableDefault, &qr);
  EncodeFn enc = (EncodeFn)fn;
  CUtensorMap mx64, mx32, mo64, mo32, mw, mxt, mot;
  make_map_touch(enc, &mxt, d_in[0]);
  make_map_touch(enc, &mot, d_out);
  make_map_2d(enc, &mx64, d_in[0], kRows, 64);
  make_map_2d(enc, &mx32, d_in[0], kRows, 32);
  make_map_2d(enc, &mo64, d_out, kRows, 64);
  make_map_2d(enc, &mo32, d_out, kRows, 32);
  {
    cuuint64_t dims[3] = {64, (cuuint64_t)kLayers * kDim, kDim / 64};
    cuuint64_t strides[2] = {kDim * 2, 128};
    cuuint32_t box[3] = {64, 32, 4};
    cuuint32_t es[3] = {1, 1, 1};
    enc(&mw, CU_TENSOR_MAP_DATA_TYPE_BFLOAT16, 3, d_in[1], dims, strides, box, es, CU_TENSOR_MAP_INTERLEAVE_NONE,
        CU_TENSOR_MAP_SWIZZLE_128B, CU_TENSOR_MAP_L2_PROMOTION_L2_128B, CU_TENSOR_MAP_FLOAT_OOB_FILL_NONE);
  }
  const __nv_bfloat16* x0 = (const __nv_bfloat16*)d_in[0];
  const __nv_bfloat16* w = (const __nv_bfloat16*)d_in[1];
  const __nv_bfloat16* b = (const __nv_bfloat16*)d_in[2];
  __nv_bfloat16* out = (__nv_bfloat16*)d_out;
  constexpr int smem = SMEM_BYTES + PROF_SMEM;
  cudaFuncSetAttribute(dcn_kernel<false>, cudaFuncAttributeMaxDynamicSharedMemorySize, smem);
  cudaFuncSetAttribute(dcn_kernel<true>, cudaFuncAttributeMaxDynamicSharedMemorySize, smem);

  cudaLaunchConfig_t cfg = {};
  cfg.gridDim = dim3(4 * kGroups + 4);
  cfg.blockDim = dim3(384);
  cfg.dynamicSmemBytes = smem;
  cudaLaunchAttribute attr;
  attr.id = cudaLaunchAttributeClusterDimension;
  attr.val.clusterDim.x = 2;
  attr.val.clusterDim.y = 1;
  attr.val.clusterDim.z = 1;
  cfg.attrs = &attr;
  cfg.numAttrs = 1;
  int clusters = 0;
  cudaOccupancyMaxActiveClusters(&clusters, dcn_kernel<false>, &cfg);
  int dev = 0, sms = 0;
  cudaGetDevice(&dev);
  cudaDeviceGetAttribute(&sms, cudaDevAttrMultiProcessorCount, dev);
  if (clusters >= 2 * kGroups) {
    const int grid = 4 * kGroups + (clusters >= 2 * kGroups + 2 ? 4 : 0);
    auto kernel = grid == sms && grid > 4 * kGroups ? dcn_kernel<true> : dcn_kernel<false>;
    kernel<<<grid, 384, smem>>>(mx64, mx32, mo64, mo32, mw, mxt, mot, x0, w, b, out);
  } else {
    dcn_fallback<<<kRows / 8, 256>>>(x0, w, b, out);
  }
}
```

```cpp
#include <cuda_runtime.h>
#include <cuda.h>
#include <cuda_bf16.h>
#include <stdint.h>

namespace dcn {

template <int TA, int TB> __device__ __forceinline__ void wgmma_ss_n256(float (&d)[128], uint64_t da, uint64_t db) {
  asm volatile("{\n.reg .pred p;\nsetp.ne.b32 p, %130, 0;\n"
    "wgmma.mma_async.sync.aligned.m64n256k16.f32.bf16.bf16 "
    "{%0, %1, %2, %3, %4, %5, %6, %7, %8, %9, %10, %11, %12, %13, %14, %15, %16, %17, %18, %19, %20, %21, %22, %23, %24, %25, %26, %27, %28, %29, %30, %31, %32, %33, %34, %35, %36, %37, %38, %39, %40, %41, %42, %43, %44, %45, %46, %47, %48, %49, %50, %51, %52, %53, %54, %55, %56, %57, %58, %59, %60, %61, %62, %63, %64, %65, %66, %67, %68, %69, %70, %71, %72, %73, %74, %75, %76, %77, %78, %79, %80, %81, %82, %83, %84, %85, %86, %87, %88, %89, %90, %91, %92, %93, %94, %95, %96, %97, %98, %99, %100, %101, %102, %103, %104, %105, %106, %107, %108, %109, %110, %111, %112, %113, %114, %115, %116, %117, %118, %119, %120, %121, %122, %123, %124, %125, %126, %127}, "
    "%128, %129, p, 1, 1, %131, %132;\n}\n"
    : "+f"(d[0]), "+f"(d[1]), "+f"(d[2]), "+f"(d[3]), "+f"(d[4]), "+f"(d[5]), "+f"(d[6]), "+f"(d[7]), "+f"(d[8]), "+f"(d[9]), "+f"(d[10]), "+f"(d[11]), "+f"(d[12]), "+f"(d[13]), "+f"(d[14]), "+f"(d[15]), "+f"(d[16]), "+f"(d[17]), "+f"(d[18]), "+f"(d[19]), "+f"(d[20]), "+f"(d[21]), "+f"(d[22]), "+f"(d[23]), "+f"(d[24]), "+f"(d[25]), "+f"(d[26]), "+f"(d[27]), "+f"(d[28]), "+f"(d[29]), "+f"(d[30]), "+f"(d[31]), "+f"(d[32]), "+f"(d[33]), "+f"(d[34]), "+f"(d[35]), "+f"(d[36]), "+f"(d[37]), "+f"(d[38]), "+f"(d[39]), "+f"(d[40]), "+f"(d[41]), "+f"(d[42]), "+f"(d[43]), "+f"(d[44]), "+f"(d[45]), "+f"(d[46]), "+f"(d[47]), "+f"(d[48]), "+f"(d[49]), "+f"(d[50]), "+f"(d[51]), "+f"(d[52]), "+f"(d[53]), "+f"(d[54]), "+f"(d[55]), "+f"(d[56]), "+f"(d[57]), "+f"(d[58]), "+f"(d[59]), "+f"(d[60]), "+f"(d[61]), "+f"(d[62]), "+f"(d[63]), "+f"(d[64]), "+f"(d[65]), "+f"(d[66]), "+f"(d[67]), "+f"(d[68]), "+f"(d[69]), "+f"(d[70]), "+f"(d[71]), "+f"(d[72]), "+f"(d[73]), "+f"(d[74]), "+f"(d[75]), "+f"(d[76]), "+f"(d[77]), "+f"(d[78]), "+f"(d[79]), "+f"(d[80]), "+f"(d[81]), "+f"(d[82]), "+f"(d[83]), "+f"(d[84]), "+f"(d[85]), "+f"(d[86]), "+f"(d[87]), "+f"(d[88]), "+f"(d[89]), "+f"(d[90]), "+f"(d[91]), "+f"(d[92]), "+f"(d[93]), "+f"(d[94]), "+f"(d[95]), "+f"(d[96]), "+f"(d[97]), "+f"(d[98]), "+f"(d[99]), "+f"(d[100]), "+f"(d[101]), "+f"(d[102]), "+f"(d[103]), "+f"(d[104]), "+f"(d[105]), "+f"(d[106]), "+f"(d[107]), "+f"(d[108]), "+f"(d[109]), "+f"(d[110]), "+f"(d[111]), "+f"(d[112]), "+f"(d[113]), "+f"(d[114]), "+f"(d[115]), "+f"(d[116]), "+f"(d[117]), "+f"(d[118]), "+f"(d[119]), "+f"(d[120]), "+f"(d[121]), "+f"(d[122]), "+f"(d[123]), "+f"(d[124]), "+f"(d[125]), "+f"(d[126]), "+f"(d[127])
    : "l"(da), "l"(db), "n"(1), "n"(TA), "n"(TB));
}

constexpr int kDim = 1024;
constexpr int kRows = 16384;
constexpr int kLayers = 6;
constexpr int kGroups = 32;
constexpr int kRounds = kRows / 128 / kGroups;
constexpr int kTiles = kRounds * kLayers;

constexpr float kOffset = 171.f / 128.f;
constexpr int kJobs = kGroups;
constexpr int kEpoch = 32;
constexpr int NA = 4;
constexpr int NB = 9;
constexpr int BPRE = 4;
constexpr int NT = 11;
constexpr int A_SLOT = 8192;
constexpr int B_SLOT = 16384;
constexpr int OFF_B = 0;
constexpr int OFF_A = OFF_B + NB * B_SLOT;
constexpr int OFF_EXTRA = OFF_A + 2 * NA * A_SLOT;
constexpr int OFF_BIAS = OFF_EXTRA + A_SLOT;
constexpr int OFF_BAR = OFF_BIAS + kLayers * 256 * 2;
constexpr int BAR_AFULL = OFF_BAR;
constexpr int BAR_BFULL = OFF_BAR + 64;
constexpr int BAR_ORDER = BAR_BFULL + NB * 8;
constexpr int BAR_XREADY = BAR_ORDER + 8;
constexpr int BAR_EXTRA = BAR_XREADY + 16;
constexpr int BAR_TOUCH = BAR_EXTRA + 16;
constexpr int BAR_BEMPTY = OFF_BAR + 3 * 64;
constexpr int BAR_BIAS = BAR_BEMPTY + NB * 8;
constexpr int BAR_PUB = BAR_BIAS + 8;
constexpr int OFF_PEER = BAR_PUB + 8;
constexpr int BAR_AEMPTY = OFF_BAR + 5 * 64;
constexpr int BAR_STAGED = OFF_BAR + 6 * 64;
constexpr int OFF_TOUCH = OFF_BAR + 8 * 64;
constexpr int SMEM_BYTES = OFF_TOUCH + 1024;
static_assert(BAR_TOUCH + 8 == OFF_BAR + 23 * 8 && NA == 4, "barrier groups");
static_assert(SMEM_BYTES <= 232448, "shared memory budget");

constexpr int kFlagSet = 4 * (kGroups + 1) * 32;
__device__ unsigned int g_flags[3 * kFlagSet];

__device__ __forceinline__ uint32_t smem_u32(const void* p) { return (uint32_t)__cvta_generic_to_shared(p); }
__device__ __forceinline__ void mbar_init(uint32_t bar, int cnt) {
  asm volatile("mbarrier.init.shared::cta.b64 [%0], %1;" ::"r"(bar), "r"(cnt) : "memory");
}
__device__ __forceinline__ void mbar_arrive(uint32_t bar) {
  asm volatile("mbarrier.arrive.shared::cta.b64 _, [%0];" ::"r"(bar) : "memory");
}
__device__ __forceinline__ uint32_t map_cta(uint32_t addr, uint32_t cta) {
  uint32_t r;
  asm volatile("mapa.shared::cluster.u32 %0, %1, %2;" : "=r"(r) : "r"(addr), "r"(cta));
  return r;
}
__device__ __forceinline__ void mbar_arrive_mapped(uint32_t cluster_addr) {
  asm volatile("mbarrier.arrive.shared::cluster.b64 _, [%0];" ::"r"(cluster_addr) : "memory");
}
__device__ __forceinline__ void mbar_wait(uint32_t bar, uint32_t parity) {
  asm volatile(
      "{\n.reg .pred p;\n.reg .u32 c;\n"
      "mbarrier.try_wait.parity.shared::cta.b64 p, [%0], %1;\n"
      "@p bra DONE;\n"
      "mov.u32 c, 0;\n"
      "LOOP:\n"
      "mbarrier.try_wait.parity.shared::cta.b64 p, [%0], %1;\n"
      "@p bra DONE;\n"
      "add.u32 c, c, 1;\n"
      "setp.lt.u32 p, c, 4194304;\n"
      "@p bra LOOP;\n"
      "trap;\n"
      "DONE:\n}"
      ::"r"(bar), "r"(parity) : "memory");
}
__device__ __forceinline__ void mbar_spin(uint32_t bar, uint32_t parity) {
  asm volatile(
      "{\n.reg .pred p;\n"
      "LOOP:\n"
      "mbarrier.try_wait.parity.shared::cta.b64 p, [%0], %1;\n"
      "@!p bra LOOP;\n}"
      ::"r"(bar), "r"(parity) : "memory");
}
#define ELECT_BEGIN "{\n.reg .pred e;\nelect.sync _|e, 0xffffffff;\n"
template <bool STREAM> __device__ __forceinline__ void expect_load_2d_e(uint32_t dst, const CUtensorMap* m, uint32_t bar, int c0, int c1) {
  if (STREAM) {
    asm volatile(ELECT_BEGIN ".reg .b64 pol;\ncreatepolicy.fractional.L2::evict_first.b64 pol, 1.0;\n"
                 "@e mbarrier.arrive.expect_tx.shared::cta.b64 _, [%2], 8192;\n"
                 "@e cp.async.bulk.tensor.2d.shared::cluster.global.mbarrier::complete_tx::bytes.L2::cache_hint [%0], [%1, {%3, %4}], [%2], pol;\n}"
                 ::"r"(dst), "l"(m), "r"(bar), "r"(c0), "r"(c1) : "memory");
  } else {
    asm volatile(ELECT_BEGIN
                 "@e mbarrier.arrive.expect_tx.shared::cta.b64 _, [%2], 8192;\n"
                 "@e cp.async.bulk.tensor.2d.shared::cluster.global.mbarrier::complete_tx::bytes [%0], [%1, {%3, %4}], [%2];\n}"
                 ::"r"(dst), "l"(m), "r"(bar), "r"(c0), "r"(c1) : "memory");
  }
}
__device__ __forceinline__ void expect_load_2d_mc_e(uint32_t dst, const CUtensorMap* m, uint32_t bar, int c0, int c1) {
  asm volatile(ELECT_BEGIN ".reg .b64 pol;\ncreatepolicy.fractional.L2::evict_first.b64 pol, 1.0;\n"
               "@e mbarrier.arrive.expect_tx.shared::cta.b64 _, [%2], 8192;\n"
               "@e cp.async.bulk.tensor.2d.shared::cluster.global.mbarrier::complete_tx::bytes.multicast::cluster.L2::cache_hint [%0], [%1, {%3, %4}], [%2], %5, pol;\n}"
               ::"r"(dst), "l"(m), "r"(bar), "r"(c0), "r"(c1), "h"((uint16_t)3) : "memory");
}
template <int BYTES>
__device__ __forceinline__ void expect_load_3d_e(uint32_t dst, const CUtensorMap* m, uint32_t bar, int c0, int c1, int c2) {
  asm volatile(ELECT_BEGIN
               "@e mbarrier.arrive.expect_tx.shared::cta.b64 _, [%2], %6;\n"
               "@e cp.async.bulk.tensor.3d.shared::cluster.global.mbarrier::complete_tx::bytes [%0], [%1, {%3, %4, %5}], [%2];\n}"
               ::"r"(dst), "l"(m), "r"(bar), "r"(c0), "r"(c1), "r"(c2), "n"(BYTES) : "memory");
}
template <bool STREAM> __device__ __forceinline__ void store_2d_e(const CUtensorMap* m, uint32_t src, int c0, int c1) {
  if (STREAM) {
    asm volatile(ELECT_BEGIN ".reg .b64 pol;\ncreatepolicy.fractional.L2::evict_first.b64 pol, 1.0;\n"
                 "@e cp.async.bulk.tensor.2d.global.shared::cta.bulk_group.L2::cache_hint [%0, {%2, %3}], [%1], pol;\n}"
                 ::"l"(m), "r"(src), "r"(c0), "r"(c1) : "memory");
  } else {
    asm volatile(ELECT_BEGIN
                 "@e cp.async.bulk.tensor.2d.global.shared::cta.bulk_group [%0, {%2, %3}], [%1];\n}"
                 ::"l"(m), "r"(src), "r"(c0), "r"(c1) : "memory");
  }
}
__device__ __forceinline__ void prefetch_2d_e(const CUtensorMap* m, int c0, int c1) {
  asm volatile(ELECT_BEGIN
               "@e cp.async.bulk.prefetch.tensor.2d.L2.global [%0, {%1, %2}];\n}"
               ::"l"(m), "r"(c0), "r"(c1) : "memory");
}
__device__ __forceinline__ void prefetch_1d_e(const void* ptr, uint32_t bytes) {
  asm volatile(ELECT_BEGIN
               "@e cp.async.bulk.prefetch.L2.global [%0], %1;\n}"
               ::"l"(ptr), "r"(bytes) : "memory");
}
__device__ __forceinline__ void load_weights_e(uint32_t dst, const CUtensorMap* m, uint32_t bar, int c0, int c1, int c2, int c3) {
  asm volatile(ELECT_BEGIN
               "@e cp.async.bulk.tensor.4d.shared::cluster.global.mbarrier::complete_tx::bytes [%0], [%1, {%3, %4, %5, %6}], [%2];\n"
               "@e mbarrier.arrive.expect_tx.shared::cta.b64 _, [%2], 16384;\n}"
               ::"r"(dst), "l"(m), "r"(bar), "r"(c0), "r"(c1), "r"(c2), "r"(c3) : "memory");
}
__device__ __forceinline__ void pace_wait(uint32_t& last, uint32_t gap) {
  asm volatile("{\n.reg .pred p;\n.reg .u32 b, d;\n"
               "AGAIN:\n"
               "mov.u32 b, %%clock;\n"
               "sub.u32 d, b, %0;\n"
               "setp.lt.u32 p, d, %1;\n"
               "@p bra.uni AGAIN;\n"
               "mov.u32 %0, b;\n}" : "+r"(last) : "r"(gap) : "memory");
}
__device__ __forceinline__ void arrive_mapped_e(uint32_t cluster_addr) {
  asm volatile(ELECT_BEGIN "@e mbarrier.arrive.shared::cluster.b64 _, [%0];\n}" ::"r"(cluster_addr) : "memory");
}
__device__ __forceinline__ void arrive_e(uint32_t bar) {
  asm volatile(ELECT_BEGIN "@e mbarrier.arrive.shared::cta.b64 _, [%0];\n}" ::"r"(bar) : "memory");
}
__device__ __forceinline__ void bulk_commit() { asm volatile("cp.async.bulk.commit_group;" ::: "memory"); }
template <int N> __device__ __forceinline__ void bulk_wait() { asm volatile("cp.async.bulk.wait_group %0;" ::"n"(N) : "memory"); }
__device__ __forceinline__ void wg_fence() { asm volatile("wgmma.fence.sync.aligned;" ::: "memory"); }
__device__ __forceinline__ void wg_commit() { asm volatile("wgmma.commit_group.sync.aligned;" ::: "memory"); }
template <int N> __device__ __forceinline__ void wg_wait() { asm volatile("wgmma.wait_group.sync.aligned %0;" ::"n"(N) : "memory"); }
__device__ __forceinline__ void fence_async_global() { asm volatile("fence.proxy.async.global;" ::: "memory"); }
__device__ __forceinline__ void st_relaxed(unsigned int* p, unsigned int v) {
  asm volatile("st.relaxed.gpu.global.u32 [%0], %1;" ::"l"(p), "r"(v) : "memory");
}
__device__ __forceinline__ unsigned int ld_acquire(const unsigned int* p) {
  unsigned int v;
  asm volatile("ld.acquire.gpu.global.u32 %0, [%1];" : "=r"(v) : "l"(p) : "memory");
  return v;
}
__device__ __forceinline__ void ldsm4(uint32_t* r, uint32_t addr) {
  asm volatile("ldmatrix.sync.aligned.m8n8.x4.shared.b16 {%0, %1, %2, %3}, [%4];"
               : "=r"(r[0]), "=r"(r[1]), "=r"(r[2]), "=r"(r[3]) : "r"(addr) : "memory");
}
__device__ __forceinline__ void stsm4(uint32_t addr, const uint32_t* r) {
  asm volatile("stmatrix.sync.aligned.m8n8.x4.shared.b16 [%0], {%1, %2, %3, %4};"
               ::"r"(addr), "r"(r[0]), "r"(r[1]), "r"(r[2]), "r"(r[3]) : "memory");
}
__device__ __forceinline__ void load_partial(float* a, uint32_t addr) {
  asm volatile("ld.shared.v4.f32 {%0, %1, %2, %3}, [%4];"
               : "+f"(a[4]), "+f"(a[5]), "+f"(a[6]), "+f"(a[7]) : "r"(addr) : "memory");
}
__device__ __forceinline__ void widen_partial(float* a) {
  asm volatile("shl.b32 %0, %4, 16;\nand.b32 %1, %4, 0xffff0000;\n"
               "shl.b32 %2, %5, 16;\nand.b32 %3, %5, 0xffff0000;\n"
               "shl.b32 %4, %6, 16;\nand.b32 %5, %6, 0xffff0000;\n"
               "shl.b32 %6, %7, 16;\nand.b32 %7, %7, 0xffff0000;"
               : "+f"(a[0]), "+f"(a[1]), "+f"(a[2]), "+f"(a[3]), "+f"(a[4]), "+f"(a[5]), "+f"(a[6]), "+f"(a[7]));
}
template <bool V> struct Flag { static constexpr bool value = V; };
__device__ __forceinline__ void fence_async_smem() { asm volatile("fence.proxy.async.shared::cta;" ::: "memory"); }
__device__ __forceinline__ void cluster_arrive_relaxed() { asm volatile("barrier.cluster.arrive.relaxed.aligned;" ::: "memory"); }
__device__ __forceinline__ void cluster_wait() { asm volatile("barrier.cluster.wait.acquire.aligned;" ::: "memory"); }
__device__ __forceinline__ void prefetch_map(const CUtensorMap* m) {
  asm volatile("prefetch.tensormap [%0];" ::"l"(m) : "memory");
}
__device__ __forceinline__ void poll_flag(const unsigned int* ptr, unsigned int target) {
  asm volatile(
      "{\n.reg .pred p;\n.reg .u32 c;\n.reg .s32 v;\n"
      "mov.u32 c, 0;\n"
      "LOOP:\n"
      "ld.acquire.gpu.global.s32 v, [%0];\n"
      "sub.s32 v, v, %1;\n"
      "setp.ge.s32 p, v, 0;\n"
      "@p bra DONE;\n"
      "add.u32 c, c, 1;\n"
      "setp.lt.u32 p, c, 4194304;\n"
      "@p bra LOOP;\n"
      "trap;\n"
      "DONE:\n}"
      ::"l"(ptr), "r"(target) : "memory");
}

__device__ __forceinline__ uint64_t desc_a(uint32_t lo) { return ((uint64_t)((1024u >> 4) | (1u << 30)) << 32) | lo; }
__device__ __forceinline__ uint64_t desc_b(uint32_t lo) { return ((uint64_t)((4096u >> 4) | (1u << 30)) << 32) | lo; }
constexpr uint32_t DESC_A_LBO = 1u << 16;
constexpr uint32_t DESC_B_LBO = (1024u >> 4) << 16;

struct Ring {
  uint32_t slot, phase;
  template <int N> __device__ __forceinline__ void next() {
    if (++slot == N) { slot = 0; phase ^= 1; }
  }
};

__device__ __forceinline__ int kgroup_col(int j, int q) {
  return q == 0 ? j : (q == 1 ? (j ^ 1) : (((j ^ 2) & ~1) + (q - 2)));
}

__device__ __forceinline__ int role_of_pair(int t) {
  const int b = t - 32, r = (b * 37) >> 8;
  const int gpc = t < 32 ? t : (t < 60 ? 1 + b - r * 7 : 0);
  const int pass = t < 32 ? t >> 3 : (t < 60 ? 4 + r : t - 58);
  return (t >> 1) == 30 ? t + 4 : pass * 8 + ((0x51703246 >> ((gpc * 4) & 31)) & 7);
}
__device__ __forceinline__ int helped_round(int grp) { return (grp & 2) ? (grp & 3) - 1 : 3; }
__device__ __forceinline__ int job_of_group(int grp) {
  return (grp & 2) ? (grp & 1) * 8 + (grp >> 2) : 16 + (grp >> 2) * 2 + (grp & 1);
}
__device__ __forceinline__ int job_row(int n) {
  const int grp = n < 16 ? (n & 7) * 4 + 2 + (n >> 3) : ((n - 16) >> 1) * 4 + (n & 1);
  return (helped_round(grp) * kGroups + grp) * 128;
}

#define PROF_START() do {} while (0)
#define PROF_END() do {} while (0)
#define PROF_SVC(idx) do {} while (0)
#define PROF(idx) do {} while (0)
#define PROF_SMEM 0

template <bool BY_SM>
__global__ void __cluster_dims__(2, 1, 1) __launch_bounds__(384, 1)
dcn_kernel(const __grid_constant__ CUtensorMap mx64, const __grid_constant__ CUtensorMap mx32,
           const __grid_constant__ CUtensorMap mo64, const __grid_constant__ CUtensorMap mo32,
           const __grid_constant__ CUtensorMap mw, const __grid_constant__ CUtensorMap mxt,
           const __grid_constant__ CUtensorMap mot, const __nv_bfloat16* __restrict__ xptr,
           const __nv_bfloat16* __restrict__ wptr, const __nv_bfloat16* __restrict__ bias, __nv_bfloat16* optr) {
  extern __shared__ __align__(1024) uint8_t smem_raw[];
  const uint32_t sb = smem_u32(smem_raw);
  PROF_START();
  const int tid = threadIdx.x;
  const __nv_bfloat16 *px = nullptr, *pw = nullptr;
  if (tid < 32) {
    const uint32_t r = blockIdx.x * 32 + tid;
    px = xptr + (size_t)r * kDim;
    pw = wptr + (size_t)((r & 1023) * 64);
    asm volatile("prefetch.global.L2 [%0];" ::"l"(px));
    asm volatile("prefetch.global.L2 [%0];" ::"l"(pw));
  }
  if (tid == 256) {
    prefetch_map(&mw);
    prefetch_map(&mx64);
    mbar_init(sb + BAR_BFULL, 1);
    mbar_init(sb + BAR_BFULL + 8, 1);
    mbar_init(sb + BAR_AFULL, 1);
    mbar_init(sb + BAR_AFULL + NA * 8, 1);
    asm volatile("fence.mbarrier_init.release.cluster;" ::: "memory");
  }
  const int wid = __shfl_sync(0xffffffffu, tid >> 5, 0);
  uint32_t place = blockIdx.x + (blockIdx.x < 8 ? 124 : -8);
  if (BY_SM) asm volatile("mov.u32 %0, %%smid;" : "=r"(place));
  const int bid = role_of_pair(place >> 1) * 2 + (place & 1);
  const int j = bid & 3;
  const int grp = bid >> 2;
  const bool helper = grp == kGroups;
  const int col0 = helper ? kgroup_col(j, 2) * 256 : 0;
  const int row0 = helper ? job_row(0) : grp * 128;
  auto first_loads = [&](int s) {
    const int col = col0 + s * 64;
    load_weights_e(sb + OFF_B + 2 * s * B_SLOT, &mw, sb + BAR_BFULL + 2 * s * 8, 0, 0, j * 4, col >> 3);
    expect_load_2d_e<false>(sb + OFF_A + s * A_SLOT, &mx64, sb + BAR_AFULL + s * 8, col, row0);
    expect_load_2d_e<false>(sb + OFF_A + (NA + s) * A_SLOT, &mx64, sb + BAR_AFULL + (NA + s) * 8, col, row0 + 64);
    load_weights_e(sb + OFF_B + (2 * s + 1) * B_SLOT, &mw, sb + BAR_BFULL + (2 * s + 1) * 8, 0, 0, j * 4, (col + 32) >> 3);
  };
  if (wid == 8) first_loads(0);
  __syncthreads();
  const int wg = wid >> 2, warp = wid & 3;
  const uint32_t rank = j & 1;
  const int short_t = ((BY_SM || gridDim.x > 4 * kGroups) && !helper) ? helped_round(grp) * kLayers : -1;

  if (wg < 2) {
    cluster_arrive_relaxed();
    asm volatile("setmaxnreg.inc.sync.aligned.u32 232;");
    if (tid < 32) asm volatile("prefetch.global.L2 [%0+128];\nprefetch.global.L2 [%1+131072];" ::"l"(px), "l"(pw));
    const int lane = tid & 31;
    const int wtid = tid & 127;
    const uint32_t abase = sb + OFF_A + wg * NA * A_SLOT;
    const uint32_t afull = sb + BAR_AFULL + wg * NA * 8;
    const uint32_t aempty = map_cta(sb + BAR_AEMPTY + wg * NA * 8, wtid == 32 ? (rank ^ 1) : rank);
    const bool rel_a = (wtid == 0) || (wtid == 32);
    const bool rel_b = (wtid == 64);
    const uint32_t frag0 = __shfl_sync(0xffffffffu, abase + ((wtid >> 5) * 16 + ((lane >> 3) & 1) * 8 + (lane & 7)) * 128 +
                                                        (((lane >> 4) ^ (lane & 7)) << 4), lane);
    const uint32_t adesc0 = ((abase & 0x3FFFF) >> 4) | DESC_A_LBO;
    const uint32_t bdesc0 = (((sb + OFF_B) & 0x3FFFF) >> 4) | DESC_B_LBO;

    uint32_t zero;
    asm volatile("mov.u32 %0, %%ctaid.y;" : "=r"(zero));
    float acc[128];
    uint32_t xr[64];
    asm volatile("st.shared.v4.f32 [%0], {%1, %1, %1, %1};" ::"r"(sb + OFF_EXTRA + wid * 16), "f"(kOffset) : "memory");
#pragma unroll
    for (int i = 0; i < 128; i += 4)
      asm volatile("ld.volatile.shared.v4.f32 {%0, %1, %2, %3}, [%4];"
                   : "=f"(acc[i]), "=f"(acc[i + 1]), "=f"(acc[i + 2]), "=f"(acc[i + 3]) : "r"(sb + OFF_EXTRA + wid * 16) : "memory");
#pragma unroll
    for (int i = 0; i < 64; i++) asm volatile("" : "=r"(xr[i]));
    Ring rb{0, 0};
    uint32_t slot_m1 = 0, slot_m2 = 0, slot_m3 = 0;
    uint32_t fpar = 0;
    int l = 0;
    bool hold = false;
    bool swap = false;
    int q_second = helper ? 3 : 1;
    int capture_q = helper ? -1 : j;

    auto release_b = [&](uint32_t slot) {
      if (rel_b) mbar_arrive(sb + BAR_BEMPTY + slot * 8);
    };
    auto release_a = [&](int s) {
      if (rel_a) mbar_arrive_mapped(aempty + s * 8);
    };
    auto chunk_staged = [&](int c) {
      __syncwarp();
      arrive_e(sb + BAR_STAGED + (wg * NA + c) * 8);
    };
    auto capture_slot = [&](int p) {
#pragma unroll
      for (int g = 0; g < 4; g++) ldsm4(&xr[(p * 4 + g) * 4], (frag0 ^ (g * 32)) + p * A_SLOT);
    };
    auto swap_half = [&](int p, int half) {
#pragma unroll
      for (int g = half * 2; g < half * 2 + 2; g++) {
        const uint32_t addr = (frag0 ^ (g * 32)) + p * A_SLOT;
        uint32_t n[4];
        ldsm4(n, addr);
        stsm4(addr, &xr[(p * 4 + g) * 4]);
#pragma unroll
        for (int i = 0; i < 4; i++) xr[(p * 4 + g) * 4 + i] = n[i];
      }
      if (half) chunk_staged(p);
    };
    auto half_step = [&](int q, int s, int h, int t, bool first) {
      if (s == 0 && h == 1 && q == 3 && wg == 1) {
        wg_wait<1>();
        release_b(slot_m2);
        wg_wait<0>();
        release_b(slot_m1);
        if (swap && q_second == 3) { swap_half(3, 0); swap_half(3, 1); }
        release_a(3);
        mbar_spin(sb + BAR_ORDER, t & 1);
      }
      if (!(first && h == 0)) mbar_spin(sb + BAR_BFULL + rb.slot * 8, rb.phase);
      const uint32_t bdesc = bdesc0 + rb.slot * (B_SLOT >> 4);
      const uint32_t adesc = adesc0 + s * (A_SLOT >> 4) + h * 4;
      wg_fence();
      wgmma_ss_n256<0, 1>(acc, desc_a(adesc), desc_b(bdesc));
      wgmma_ss_n256<0, 1>(acc, desc_a(adesc + 2), desc_b(bdesc + 512));
      wg_commit();
      slot_m3 = slot_m2;
      slot_m2 = slot_m1;
      slot_m1 = rb.slot;
      rb.next<NB>();
      if (s == 3 && h == 1 && q == 3 && wg == 0 && wtid == 96) mbar_arrive(sb + BAR_ORDER);
    };
    auto retire = [&](int q, int s, int h, bool first) {
      if (h == 1 && q == capture_q) capture_slot(s);
      const bool drained = s * 2 + h >= 1 && s * 2 + h <= 2 && q == 3 && wg == 1;
      if (!first && !drained) {
        wg_wait<2>();
        release_b(slot_m3);
        if (h == 1) {
          if (s == 0 || q < 3 || hold) release_a((s + 3) & 3);
          if ((s == 0 || q == 0) && swap && q == (s == 0 ? q_second : 0)) swap_half((s + 3) & 3, 0);
        } else {
          if ((s <= 1) != (q == 0) && swap && q == (s <= 1 ? q_second : 0)) swap_half((s + 2) & 3, 1);
        }
      }
    };

    cluster_wait();
    const int ntiles = helper ? kJobs : kTiles;
    mbar_spin(afull, 0);
    half_step(0, 0, 0, 0, false);
#pragma unroll 1
    for (int t = 0;; t++) {
      hold = (helper || l == kLayers - 1) && (t + 1 < ntiles);
      PROF(t * 32 + wg * 16 + 0);
#pragma unroll
      for (int s = 0; s < 4; s++) {
        if (s > 0) {
          if (l == 0) mbar_spin(afull + s * 8, fpar);
          PROF(t * 32 + wg * 16 + 8 + s);
          half_step(0, s, 0, t, false);
        }
        retire(0, s, 0, s == 0);
        half_step(0, s, 1, t, s == 0);
        retire(0, s, 1, s == 0);
      }
      if (l == 0) fpar ^= 1;
      PROF(t * 32 + wg * 16 + 1);
#pragma unroll 1
      for (int q = q_second; q < 4; q++) {
#pragma unroll
        for (int s = 0; s < 4; s++) {
          mbar_spin(afull + s * 8, fpar);
          if (s == 0) PROF(t * 32 + wg * 16 + 3 + q);
          half_step(q, s, 0, t, false);
          retire(q, s, 0, false);
          half_step(q, s, 1, t, false);
          retire(q, s, 1, false);
        }
        fpar ^= 1;
      }
      if (t == 0 && !helper) mbar_spin(sb + BAR_BIAS, 0);
      const uint32_t bl = sb + OFF_BIAS + l * 512 + (lane & 3) * 16;
      uint32_t bq[8][4];
      auto load_bias = [&](int U) {
        asm volatile("ld.shared.v4.u32 {%0, %1, %2, %3}, [%4];"
                     : "=r"(bq[U][0]), "=r"(bq[U][1]), "=r"(bq[U][2]), "=r"(bq[U][3]) : "r"(bl + U * 64));
      };
#pragma unroll
      for (int U = 0; U < BPRE; U++) load_bias(U);
      uint32_t fa[4];
#pragma unroll
      for (int g = 0; g < 4; g++) asm volatile("xor.b32 %0, %1, %2;" : "=r"(fa[g]) : "r"(frag0), "r"(g * 32));
      wg_wait<1>();
      release_b(slot_m2);
      if (t + 1 < ntiles) mbar_spin(sb + BAR_BFULL + rb.slot * 8, rb.phase);
      wg_wait<0>();
#pragma unroll
      for (int i = 0; i < 128; i++) asm volatile("" : "+f"(acc[i]) :: "memory");
      release_b(slot_m1);
      if (hold) release_a(3);
      PROF(t * 32 + wg * 16 + 2);

      auto pack = [&](int i) {
        uint32_t v;
        asm("cvt.rn.bf16x2.f32 %0, %1, %2;" : "=r"(v) : "f"(acc[i * 2 + 1]), "f"(acc[i * 2]));
        return v;
      };
      auto cross = [&](int T, int i) {
        uint32_t y, o;
        asm("mul.rn.bf16x2 %0, %1, %2;" : "=r"(y) : "r"(xr[T * 4 + i]), "r"(bq[T >> 1][(T & 1) * 2 + (i >> 1)]));
        asm("fma.rn.bf16x2 %0, %1, %2, %3;" : "=r"(o) : "r"(xr[T * 4 + i]), "r"(pack(T * 4 + i)), "r"(y));
        return o;
      };
      auto reset_acc = [&](int T) {
#pragma unroll
        for (int i = T * 8; i < T * 8 + 8; i++)
          asm("{\n.reg .u32 a, c;\nmov.b32 a, %0;\nmov.b32 c, %2;\nmad.lo.u32 a, a, %1, c;\nmov.b32 %0, a;\n}"
              : "+f"(acc[i]) : "r"(zero), "f"(kOffset));
      };
      if (helper) {
        __nv_bfloat16* dst = optr + (size_t)(job_row(t) + (tid >> 5) * 16 + (lane >> 3)) * kDim + j * 256 + (lane & 7) * 8;
        uint64_t pol;
        asm volatile("createpolicy.fractional.L2::evict_first.b64 %0, 1.0;" : "=l"(pol));
#pragma unroll
        for (int T = 0; T < 16; T++) {
          asm volatile("st.global.L2::cache_hint.v4.b32 [%0], {%1, %2, %3, %4}, %5;"
                       ::"l"(dst + (T & 3) * 4 * kDim + (T >> 2) * 64), "r"(pack(T * 4)), "r"(pack(T * 4 + 1)),
                         "r"(pack(T * 4 + 2)), "r"(pack(T * 4 + 3)), "l"(pol) : "memory");
          reset_acc(T);
        }
        asm volatile("bar.sync %0, 128;" ::"r"(wg + 1) : "memory");
        if (wtid == 0) mbar_arrive(sb + BAR_PUB);
      } else if (hold) {
        const bool inject = t + 1 == short_t;
        const uint32_t prow = ((wtid >> 5) * 16 + (lane >> 3)) * 128 + (((lane & 7) ^ (lane >> 3)) << 4);
#pragma unroll
        for (int T = 0; T < 16; T++) {
#pragma unroll
          for (int i = 0; i < 4; i++) xr[T * 4 + i] = cross(T, i);
          if ((T & 1) && (T >> 1) + BPRE < 8) load_bias((T >> 1) + BPRE);
          if ((T & 3) == 3 && !inject) {
#pragma unroll
            for (int g = T - 3; g <= T; g++) reset_acc(g);
          }
          if ((T & 3) == 3 && inject) {
            const int c = T >> 2;
            if (c > 0) mbar_spin(afull + c * 8, fpar);
            else mbar_spin(sb + BAR_EXTRA + wg * 8, 0);
            const uint32_t src = c > 0 ? abase + c * A_SLOT : sb + OFF_EXTRA;
#pragma unroll
            for (int g = 0; g < 4; g++) load_partial(&acc[(c * 4 + g) * 8], src + (prow ^ ((g & 1) * 64)) + g * 512);
            chunk_staged(c);
#pragma unroll
            for (int g = 0; g < 16; g++)
              if ((g >> 2) == c - 1 || (c == 3 && (g >> 2) == 3)) widen_partial(&acc[g * 8]);
            PROF(t * 32 + wg * 16 + 12 + c);
          }
        }
        if (inject) fpar ^= 1;
      } else {
#pragma unroll
        for (int T = 0; T < 16; T++) {
          uint32_t o[4];
#pragma unroll
          for (int i = 0; i < 4; i++) o[i] = cross(T, i);
          stsm4(fa[T & 3] + (T >> 2) * A_SLOT, o);
          if ((T & 3) == 3) chunk_staged(T >> 2);
          if ((T & 1) && (T >> 1) + BPRE < 8) load_bias((T >> 1) + BPRE);
        }
        PROF(t * 32 + wg * 16 + 7);
        fence_async_smem();
        asm volatile("bar.sync %0, 128;" ::"r"(wg + 1) : "memory");
      }
      PROF(t * 32 + wg * 16 + 3);
      if (t + 1 == ntiles) break;
      if (hold) mbar_spin(afull, fpar);
      half_step(0, 0, 0, t, true);
      if (helper || ++l == kLayers) l = 0;
      swap = hold && !helper;
      q_second = (helper || t + 1 == short_t) ? 3 : 1;
      capture_q = -1;
    }
  } else {
    asm volatile("setmaxnreg.dec.sync.aligned.u32 40;");
    if (tid == 256) {
#pragma unroll
      for (int i = 0; i < 23; i++)
        if (i != 0 && i != NA && i != 8 && i != 9) mbar_init(sb + OFF_BAR + i * 8, 1);
      asm volatile("fence.mbarrier_init.release.cluster;" ::: "memory");
    }
    if (tid == 288) {
#pragma unroll
      for (int i = 0; i < NB + 2; i++) mbar_init(sb + BAR_BEMPTY + i * 8, 2);
#pragma unroll
      for (int i = 0; i < 2 * NA; i++) { mbar_init(sb + BAR_AEMPTY + i * 8, 2); mbar_init(sb + BAR_STAGED + i * 8, 4); }
      asm volatile("fence.mbarrier_init.release.cluster;" ::: "memory");
    }
    __syncwarp();
    cluster_arrive_relaxed();
#pragma unroll 1
    for (int s = warp == 0 ? 1 : 4; s < 4; s++) first_loads(s);
    cluster_wait();
    if (warp) mbar_wait(sb + BAR_AFULL + (warp & 2) * 16, 0);
    if (warp == 0) {
      if ((sb & 1023) || bid >= 4 * (kGroups + 1)) asm volatile("trap;");
      uint32_t zero, zero2;
      asm volatile("mov.u32 %0, %%ctaid.y;\nmov.u32 %1, %%ctaid.z;" : "=r"(zero), "=r"(zero2));
      const CUtensorMap* mwp = (const CUtensorMap*)((const char*)&mw + zero);
      uint32_t dst = sb + OFF_B + 8 * B_SLOT, bar = sb + BAR_BFULL + 8 * 8, phase = 1;
      int c = 256;
      int mask = helper ? ((j & 2) ^ 2) << 8 : 0;
      int group = (c ^ mask) >> 3;
      const uint32_t relaxed = helper ? 1024 : (NT - 2) * 32;
      int left = helper ? kJobs : kTiles;
#pragma unroll 1
      for (;;) {
        mbar_spin(bar + (BAR_BEMPTY - BAR_BFULL), phase);
        if ((uint32_t)((c - 64) & 1023) >= relaxed) __nanosleep(128);
        load_weights_e(dst, mwp, bar, zero, zero2, j * 4, group);
        c += 32;
        dst += B_SLOT;
        bar += 8;
        if (bar == sb + BAR_BFULL + NB * 8) { bar = sb + BAR_BFULL; dst = sb + OFF_B; phase ^= 1; }
        if ((c & 511) == 0) {
          if ((c & 512) && (helper || kTiles - left == short_t)) c += 512;
          if (c & 512) {
            mask &= 512;
          } else {
            if (--left == 0) break;
            if (helper || c == kLayers * kDim) c = 0;
            if (!helper) mask = j << 8;
          }
        }
        group = (c ^ mask) >> 3;
      }
    } else if (warp <= 2) {
      const int w = warp - 1;
      const uint32_t abase = sb + OFF_A + w * NA * A_SLOT;
      const uint32_t fullb = sb + BAR_AFULL + w * NA * 8;
      const uint32_t emptyb = sb + BAR_AEMPTY + w * NA * 8;
      const uint32_t stagedb = sb + BAR_STAGED + w * NA * 8;
      const unsigned int base = __shfl_sync(0xffffffffu, *(volatile unsigned int*)(g_flags + bid * 32), 0);
      uint32_t epar = 0;
      uint32_t spar = 0;
      uint32_t last = 0;
      auto refill = [&](const CUtensorMap* m, int col, int row) {
#pragma unroll 1
        for (int s = 0; s < 4; s++) {
          mbar_wait(emptyb + s * 8, epar);
          expect_load_2d_e<false>(abase + s * A_SLOT, m, fullb + s * 8, col + s * 64, row);
        }
        epar ^= 1;
      };
      auto store_refill = [&](int out_row, int col, int row, bool last_read) {
#pragma unroll 1
        for (int s = 0; s < 4; s++) {
          mbar_wait(stagedb + s * 8, spar);
          fence_async_smem();
          store_2d_e<true>(&mo64, abase + s * A_SLOT, j * 256 + s * 64, out_row);
          bulk_commit();
          bulk_wait<0>();
          __syncwarp();
          mbar_wait(emptyb + s * 8, epar);
          if (last_read) expect_load_2d_e<true>(abase + s * A_SLOT, &mx64, fullb + s * 8, col + s * 64, row);
          else expect_load_2d_e<false>(abase + s * A_SLOT, &mx64, fullb + s * 8, col + s * 64, row);
        }
        spar ^= 1;
        epar ^= 1;
      };
      auto store_tile = [&](auto stream, int out_row) {
#pragma unroll 1
        for (int c = 0; c < 4; c++) {
          mbar_wait(stagedb + c * 8, spar);
          fence_async_smem();
          if (!decltype(stream)::value) pace_wait(last, w ? 640 : 512);
          store_2d_e<decltype(stream)::value>(&mo64, abase + c * A_SLOT, j * 256 + c * 64, out_row);
        }
        spar ^= 1;
        bulk_commit();
        bulk_wait<0>();
        __syncwarp();
      };
      auto refill_shared = [&](const CUtensorMap* m32, int col, int row) {
#pragma unroll 1
        for (int s = 0; s < 4; s++) {
          mbar_wait(emptyb + s * 8, epar);
          expect_load_2d_mc_e(abase + s * A_SLOT + rank * 4096, m32, fullb + s * 8, col + s * 64, row + rank * 32);
        }
        epar ^= 1;
      };
      if (helper) {
#pragma unroll 1
        for (int h = 1; h < 2 * kJobs; h++) refill_shared(&mx32, col0 + (h & 1) * 256, job_row(h >> 1) + w * 64);
      } else {
        const uint32_t xready_peer = map_cta(sb + BAR_XREADY + w * 8, rank ^ 1);
        const unsigned int* oflag = g_flags + (grp * 4 + kgroup_col(j, 2)) * 32;
        unsigned int* done_mine = g_flags + kFlagSet + (bid * 2 + w) * 32;
        const unsigned int* done_peer = g_flags + kFlagSet + ((bid ^ 2) * 2 + w) * 32;
        uint32_t nx = 0;
        uint32_t fpar = 0;
#pragma unroll 1
        for (int rd = 0; rd < kRounds; rd++) {
          const int xrow = (rd * kGroups + grp) * 128 + w * 64;
          if (rd == 0) {
            refill(&mx64, 256, xrow);
          } else {
            poll_flag(done_peer, base + nx);
            store_refill(xrow - kGroups * 128, (j ^ 1) * 256, xrow, rd * kLayers == short_t);
          }
          if (rd * kLayers != short_t) {
#pragma unroll 1
            for (int h = 0; h < 2; h++) refill_shared(&mx32, (kgroup_col(rd == 0 ? 0 : j, 2) + h) * 256, xrow);
          }
          fpar ^= 1;
#pragma unroll 1
          for (int l = 1; l < kLayers; l++) {
            if (l > 1) poll_flag(done_peer, base + nx);
            store_tile(Flag<false>(), xrow);
            PROF_SVC((rd * kLayers + l - 1) * 2 + w);
            arrive_mapped_e(xready_peer);
            arrive_e(sb + BAR_PUB);
            mbar_wait(sb + BAR_XREADY + w * 8, nx & 1);
            fence_async_global();
            refill(&mo64, (j ^ 1) * 256, xrow);
            if (rd * kLayers + l + 1 == short_t) {
              poll_flag(g_flags + (4 * kGroups + j) * 32, base + job_of_group(grp) + 1);
              fence_async_global();
              if (w == 0) expect_load_2d_e<false>(sb + OFF_EXTRA, &mo64, sb + BAR_EXTRA, j * 256, xrow + kGroups * 128);
            }
#pragma unroll 1
            for (int h = 0; h < 2; h++) {
              poll_flag(oflag + h * 32, base + nx + 1);
              fence_async_global();
              refill_shared(&mo32, (kgroup_col(j, 2) + h) * 256, xrow);
            }
            fpar ^= 1;
            if (rank) {
#pragma unroll 1
              for (int s = 0; s < 4; s++) mbar_wait(fullb + s * 8, fpar);
            }
            nx++;
            if ((tid & 31) == 0) st_relaxed(done_mine, base + (nx == kRounds * (kLayers - 1) ? kEpoch : nx));
            __syncwarp();
          }
          const int nrow = xrow + kGroups * 128;
          if (rd + 1 == kRounds) {
            poll_flag(done_peer, base + nx);
            store_tile(Flag<true>(), xrow);
          } else if ((rd + 1) * kLayers == short_t) {
#pragma unroll 1
            for (int s = 0; s < 4; s++) {
              mbar_wait(emptyb + s * 8, epar);
              if (s == 0) {
                arrive_e(fullb);
                mbar_wait(fullb, fpar ^ 1);
              }
              expect_load_2d_e<false>(abase + s * A_SLOT, s > 0 ? &mo64 : &mx64, fullb + s * 8, j * 256 + s * 64, nrow);
            }
            epar ^= 1;
#pragma unroll 1
            for (int s = 0; s < 4; s++) {
              mbar_wait(stagedb + s * 8, spar);
              fence_async_smem();
              if (s > 0) expect_load_2d_e<false>(abase + s * A_SLOT, &mx64, fullb + s * 8, j * 256 + s * 64, nrow);
              else if (w == 0) expect_load_2d_e<false>(sb + OFF_EXTRA, &mo64, sb + BAR_EXTRA + 8, j * 256, nrow + 64);
            }
            spar ^= 1;
          } else {
            refill(&mx64, j * 256, nrow);
            fpar ^= 1;
          }
          PROF_SVC((rd * kLayers + kLayers - 1) * 2 + w);
        }
      }
    } else {
      const int lane = tid & 31;
      unsigned int* myflag = g_flags + bid * 32;
      if (lane == 0) { prefetch_map(&mx32); prefetch_map(&mo64); prefetch_map(&mo32); }
      const unsigned int base = *(volatile unsigned int*)myflag;
      if (BY_SM)
        asm volatile("st.volatile.shared::cluster.u32 [%0], %1;"
                     ::"r"(map_cta(sb + OFF_PEER, ~blockIdx.x & 1)), "r"(bid + 1) : "memory");
      auto publish = [&](uint32_t n, uint32_t value) {
        mbar_wait(sb + BAR_PUB, n & 1);
        asm volatile("fence.acq_rel.gpu;" ::: "memory");
        if (BY_SM && n == 1)
          asm volatile("{\n.reg .pred p;\n.reg .u32 v;\nld.volatile.shared.u32 v, [%0];\nsetp.ne.u32 p, v, %1;\n@p trap;\n}"
                       ::"r"(sb + OFF_PEER), "r"(((bid & ~1) | (~blockIdx.x & 1)) + 1) : "memory");
        if (lane == 0) st_relaxed(myflag, base + value);
        __syncwarp();
      };
      if (helper) {
#pragma unroll 1
        for (int n = 0; n < kJobs; n++) {
          if (n + 2 < kJobs) {
            const int row = job_row(n + 2);
#pragma unroll 1
            for (int i = 0; i < 8; i++) prefetch_2d_e(&mx64, col0 + rank * 256 + (i & 3) * 64, row + (i >> 2) * 64);
          }
          publish(n, n + 1);
        }
      } else {
        {
          float c[8];
#pragma unroll
          for (int i = 0; i < 8; i++) c[i] = 1.f - kOffset;
#pragma unroll 1
          for (int l = 0; l < kLayers; l++) {
            const uint4 v = *reinterpret_cast<const uint4*>(bias + l * kDim + j * 256 + lane * 8);
            const uint32_t u[4] = {v.x, v.y, v.z, v.w};
#pragma unroll
            for (int i = 0; i < 4; i++) {
              c[2 * i] += __uint_as_float(u[i] << 16);
              c[2 * i + 1] += __uint_as_float(u[i] & 0xffff0000u);
              uint32_t pk;
              asm("cvt.rn.bf16x2.f32 %0, %1, %2;" : "=r"(pk) : "f"(c[2 * i + 1]), "f"(c[2 * i]));
              asm volatile("st.shared.u32 [%0], %1;" ::"r"(sb + OFF_BIAS + l * 512 + (lane >> 2) * 64 + i * 16 + (lane & 3) * 4),
                           "r"(pk) : "memory");
            }
          }
          __syncwarp();
          if (lane < 2) mbar_arrive(sb + BAR_BIAS);
        }
        const __nv_bfloat16* wslice = wptr + bid * 8192;
        prefetch_1d_e(wslice + kDim * kDim, 16384);
        uint32_t nx = 0, tpar = 1;
#pragma unroll 1
        for (int rd = 0; rd < kRounds; rd++) {
#pragma unroll 1
          for (int l = 1; l < kLayers; l++) {
            publish(nx, nx + 1 == kRounds * (kLayers - 1) ? kEpoch : nx + 1);
            nx++;
            if (l < kLayers - 1 && rd == 0) prefetch_1d_e(wslice + (l + 1) * kDim * kDim, 16384);
            if (l >= kLayers - 2 && rd + 1 < kRounds) {
              const int nrow = ((rd + 1) * kGroups + grp) * 128;
              const int count = (rd + 1) * kLayers == short_t ? 8 : 4;
              const int first = (l - (kLayers - 2)) * count;
              bool ready = true;
              if (first == 8) {
                const unsigned int v = ld_acquire(g_flags + (4 * kGroups + j) * 32);
                ready = __shfl_sync(0xffffffffu, (int)(v - (base + job_of_group(grp) + 1)) >= 0, 0);
                fence_async_global();
              }
#pragma unroll 1
              for (int i = first; ready && i < first + count; i++) {
                mbar_wait(sb + BAR_TOUCH, tpar);
                tpar ^= 1;
                expect_load_3d_e<1024>(sb + OFF_TOUCH, i < 8 ? &mxt : &mot, sb + BAR_TOUCH, 0, j * 4, nrow + (i & 7) * 16);
                __nanosleep(count == 8 ? 300 : 600);
              }
            }
          }
        }
      }
    }
    if (warp == (helper ? 3 : 2)) PROF_END();
  }
}

__global__ void __launch_bounds__(256) dcn_fallback(const __nv_bfloat16* __restrict__ x0, const __nv_bfloat16* __restrict__ w,
                                                    const __nv_bfloat16* __restrict__ b, __nv_bfloat16* __restrict__ out) {
  __shared__ float xs[8][kDim];
  const size_t r0 = (size_t)blockIdx.x * 8;
  for (int i = threadIdx.x; i < 8 * kDim; i += 256) xs[i / kDim][i % kDim] = __bfloat162float(x0[r0 * kDim + i]);
  __syncthreads();
  for (int l = 0; l < kLayers; l++) {
    float a[4][8] = {};
    for (int k = 0; k < kDim; k++) {
#pragma unroll
      for (int c = 0; c < 4; c++) {
        const float wv = __bfloat162float(w[((size_t)l * kDim + k) * kDim + c * 256 + threadIdx.x]);
#pragma unroll
        for (int r = 0; r < 8; r++) a[c][r] += xs[r][k] * wv;
      }
    }
    __syncthreads();
#pragma unroll
    for (int c = 0; c < 4; c++) {
      const int n = c * 256 + threadIdx.x;
#pragma unroll
      for (int r = 0; r < 8; r++) {
        const float v = __bfloat162float(x0[(r0 + r) * kDim + n]) * (a[c][r] + __bfloat162float(b[l * kDim + n])) + xs[r][n];
        xs[r][n] = __bfloat162float(__float2bfloat16(v));
      }
    }
    __syncthreads();
  }
  for (int i = threadIdx.x; i < 8 * kDim; i += 256) out[r0 * kDim + i] = __float2bfloat16(xs[i / kDim][i % kDim]);
}

typedef CUresult (*EncodeFn)(CUtensorMap*, CUtensorMapDataType, cuuint32_t, void*, const cuuint64_t*, const cuuint64_t*,
                             const cuuint32_t*, const cuuint32_t*, CUtensorMapInterleave, CUtensorMapSwizzle,
                             CUtensorMapL2promotion, CUtensorMapFloatOOBfill);

static void make_map_2d(EncodeFn enc, CUtensorMap* m, void* ptr, uint64_t rows, uint32_t box_rows) {
  cuuint64_t dims[2] = {(cuuint64_t)kDim, rows};
  cuuint64_t strides[1] = {kDim * 2};
  cuuint32_t box[2] = {64, box_rows};
  cuuint32_t es[2] = {1, 1};
  enc(m, CU_TENSOR_MAP_DATA_TYPE_BFLOAT16, 2, ptr, dims, strides, box, es, CU_TENSOR_MAP_INTERLEAVE_NONE,
      CU_TENSOR_MAP_SWIZZLE_128B, CU_TENSOR_MAP_L2_PROMOTION_L2_128B, CU_TENSOR_MAP_FLOAT_OOB_FILL_NONE);
}

static void make_map_touch(EncodeFn enc, CUtensorMap* m, void* ptr) {
  cuuint64_t dims[3] = {64, kDim / 64, kRows};
  cuuint64_t strides[2] = {128, kDim * 2};
  cuuint32_t box[3] = {8, 4, 16};
  cuuint32_t es[3] = {1, 1, 1};
  enc(m, CU_TENSOR_MAP_DATA_TYPE_BFLOAT16, 3, ptr, dims, strides, box, es, CU_TENSOR_MAP_INTERLEAVE_NONE,
      CU_TENSOR_MAP_SWIZZLE_NONE, CU_TENSOR_MAP_L2_PROMOTION_L2_128B, CU_TENSOR_MAP_FLOAT_OOB_FILL_NONE);
}

}

extern "C" void kernel_launch(void* const* d_in, const int* in_sizes, int n_in, void* d_out, int out_size) {
  using namespace dcn;
  (void)in_sizes; (void)n_in; (void)out_size;
  void* fn = nullptr;
  cudaDriverEntryPointQueryResult qr;
  cudaGetDriverEntryPoint("cuTensorMapEncodeTiled", &fn, cudaEnableDefault, &qr);
  EncodeFn enc = (EncodeFn)fn;
  CUtensorMap mx64, mx32, mo64, mo32, mw, mxt, mot;
  make_map_touch(enc, &mxt, d_in[0]);
  make_map_touch(enc, &mot, d_out);
  make_map_2d(enc, &mx64, d_in[0], kRows, 64);
  make_map_2d(enc, &mx32, d_in[0], kRows, 32);
  make_map_2d(enc, &mo64, d_out, kRows, 64);
  make_map_2d(enc, &mo32, d_out, kRows, 32);
  {
    cuuint64_t dims[4] = {64, 8, kDim / 64, (cuuint64_t)kLayers * kDim / 8};
    cuuint64_t strides[3] = {kDim * 2, 128, kDim * 16};
    cuuint32_t box[4] = {64, 8, 4, 4};
    cuuint32_t es[4] = {1, 1, 1, 1};
    enc(&mw, CU_TENSOR_MAP_DATA_TYPE_BFLOAT16, 4, d_in[1], dims, strides, box, es, CU_TENSOR_MAP_INTERLEAVE_NONE,
        CU_TENSOR_MAP_SWIZZLE_128B, CU_TENSOR_MAP_L2_PROMOTION_L2_128B, CU_TENSOR_MAP_FLOAT_OOB_FILL_NONE);
  }
  const __nv_bfloat16* x0 = (const __nv_bfloat16*)d_in[0];
  const __nv_bfloat16* w = (const __nv_bfloat16*)d_in[1];
  const __nv_bfloat16* b = (const __nv_bfloat16*)d_in[2];
  __nv_bfloat16* out = (__nv_bfloat16*)d_out;
  constexpr int smem = SMEM_BYTES + PROF_SMEM;
  cudaFuncSetAttribute(dcn_kernel<false>, cudaFuncAttributeMaxDynamicSharedMemorySize, smem);
  cudaFuncSetAttribute(dcn_kernel<true>, cudaFuncAttributeMaxDynamicSharedMemorySize, smem);

  cudaLaunchConfig_t cfg = {};
  cfg.gridDim = dim3(4 * kGroups + 4);
  cfg.blockDim = dim3(384);
  cfg.dynamicSmemBytes = smem;
  cudaLaunchAttribute attr;
  attr.id = cudaLaunchAttributeClusterDimension;
  attr.val.clusterDim.x = 2;
  attr.val.clusterDim.y = 1;
  attr.val.clusterDim.z = 1;
  cfg.attrs = &attr;
  cfg.numAttrs = 1;
  int clusters = 0;
  cudaOccupancyMaxActiveClusters(&clusters, dcn_kernel<false>, &cfg);
  int dev = 0, sms = 0;
  cudaGetDevice(&dev);
  cudaDeviceGetAttribute(&sms, cudaDevAttrMultiProcessorCount, dev);
  if (clusters >= 2 * kGroups) {
    const int grid = 4 * kGroups + (clusters >= 2 * kGroups + 2 ? 4 : 0);
    auto kernel = grid == sms && grid > 4 * kGroups ? dcn_kernel<true> : dcn_kernel<false>;
    kernel<<<grid, 384, smem>>>(mx64, mx32, mo64, mo32, mw, mxt, mot, x0, w, b, out);
  } else {
    dcn_fallback<<<kRows / 8, 256>>>(x0, w, b, out);
  }
}
```
